```python
import torch

def _softmax(x, axis=-1):
    return torch.softmax(x, dim=axis)
def _gelu(x):
    return torch.nn.functional.gelu(x, approximate="tanh")
def _silu(x):
    return torch.nn.functional.silu(x)
def _sigmoid(x):
    return torch.sigmoid(x)
def _layernorm(x, axis=-1, eps=1e-5):
    m = x.mean(dim=axis, keepdim=True)
    v = x.var(dim=axis, keepdim=True, unbiased=False)
    return (x - m) / torch.sqrt(v + eps)
def _scatter_add(tgt, idx, src, axis=0):
    return tgt.clone().index_add_(axis, idx, src)
def _segment_sum(src, seg, n):
    out = torch.zeros((n,) + src.shape[1:], dtype=src.dtype)
    return out.index_add_(0, seg, src)
def _pad(x, pw):
    flat = tuple(v for pair in reversed(pw) for v in pair)
    return torch.nn.functional.pad(x, flat)

kernel_name = 'parallel_sum__ssm_conv_s4__dense_activation_relu__prompt'

def setup_inputs():

    _w = (lambda a: (lambda t: t.to(torch.bfloat16) if t.is_floating_point() else t)(torch.as_tensor(a)))
    def _A_setup():
        B, L, D, N = 1, 2048, 512, 128
        A_re = -(lambda _x: torch.exp(torch.as_tensor(_x)))((lambda *s: torch.randn(*s, dtype=torch.bfloat16) * 3.2)(D, N))
        A_im = torch.pi * (lambda *s: torch.randn(*s, dtype=torch.bfloat16) * 0.1)(D, N)
        B_re = (lambda *s: torch.randn(*s, dtype=torch.bfloat16) * 0.4)(D, N)
        B_im = (lambda *s: torch.randn(*s, dtype=torch.bfloat16) * 0.4)(D, N)
        C_re = (lambda *s: torch.randn(*s, dtype=torch.bfloat16) * 0.4)(D, N)
        C_im = (lambda *s: torch.randn(*s, dtype=torch.bfloat16) * 0.4)(D, N)
        log_dt = (lambda *s: torch.randn(*s, dtype=torch.bfloat16) * 0.1)(D) * 0.5 - 4.0
        Dskip = (lambda *s: torch.randn(*s, dtype=torch.bfloat16) * 0.2)(D)
        return {
            "u": _w((lambda *s: torch.randn(*s, dtype=torch.bfloat16) * 0.05)(B, L, D)),
            "A_re": _w(A_re),
            "A_im": _w(A_im),
            "B_re": _w(B_re),
            "B_im": _w(B_im),
            "C_re": _w(C_re),
            "C_im": _w(C_im),
            "log_dt": _w(log_dt),
            "Dskip": _w(Dskip),
        }
    _A_in = _A_setup()

    def _B_setup():
        B, S, D, Dff = 1, 2048, 512, 1376
        return {
            "x": _w((lambda *s: torch.randn(*s, dtype=torch.bfloat16) * 0.05)(B, S, D)),
            "w1": _w((lambda *s: torch.randn(*s, dtype=torch.bfloat16) * 0.05)(D, Dff)),
            "w2": _w((lambda *s: torch.randn(*s, dtype=torch.bfloat16) * 0.05)(Dff, D)),
        }
    _B_in = _B_setup()

    return {
        "A_u": _A_in["u"],
        "A_A_re": _A_in["A_re"],
        "A_A_im": _A_in["A_im"],
        "A_B_re": _A_in["B_re"],
        "A_B_im": _A_in["B_im"],
        "A_C_re": _A_in["C_re"],
        "A_C_im": _A_in["C_im"],
        "A_log_dt": _A_in["log_dt"],
        "A_Dskip": _A_in["Dskip"],
        "B_x": _B_in["x"],
        "B_w1": _B_in["w1"],
        "B_w2": _B_in["w2"],
    }

def reference(A_u, A_A_re, A_A_im, A_B_re, A_B_im, A_C_re, A_C_im, A_log_dt, A_Dskip, B_x, B_w1, B_w2):
    def _A_ref(u, A_re, A_im, B_re, B_im, C_re, C_im, log_dt, Dskip):
        Bsz, L, D = u.shape
        dt = torch.exp(log_dt)[:, None]
        A = A_re + 1j * A_im
        Bc = B_re + 1j * B_im
        Cc = C_re + 1j * C_im
        logdA = dt * A
        dB = dt * Bc
        l = (lambda x, dt: x.to(dt))(torch.arange(L), A_re.dtype)
        P = torch.exp(logdA[:, :, None] * l[None, None, :])
        K = torch.einsum("dn,dnl,dn->dl", Cc, P, dB).real
        L2 = 2 * L
        Kp = _pad(K, ((0, 0), (0, L)))
        up = (lambda x, *d: x.permute(*d))(u, 0, 2, 1)
        up = _pad(up, ((0, 0), (0, 0), (0, L)))
        Kf = (lambda x, axes=(-2,-1): torch.fft.rfft2(x.float(), dim=axes))(Kp[:, None, :], axes=(-2, -1))
        Uf = (lambda x, axes=(-2,-1): torch.fft.rfft2(x.float(), dim=axes))(up[:, :, None, :], axes=(-2, -1))
        Yf = Uf * Kf[None, :, :, :]
        y = (lambda x, s, axes=(-2,-1): torch.fft.irfft2(x, s=s, dim=axes).to(torch.bfloat16))(Yf, (1, L2), axes=(-2, -1))[:, :, 0, :L]
        y = (lambda x, *d: x.permute(*d))(y, 0, 2, 1) + u * Dskip[None, None, :]
        return y

    def _B_ref(x, w1, w2):
        h = torch.einsum("bsd,df->bsf", x, w1)
        zero = torch.zeros_like(h)
        h = torch.maximum(h, zero)
        return torch.einsum("bsf,fd->bsd", h, w2)

    x = A_u
    xn = _layernorm(x, axis=-1)
    return x + _A_ref(xn, A_A_re, A_A_im, A_B_re, A_B_im, A_C_re, A_C_im, A_log_dt, A_Dskip) + _B_ref(xn, B_w1, B_w2)
```

```cpp
#include <cuda_runtime.h>
#include <cuda_bf16.h>
#include <cuda.h>
#include <stdint.h>

#define STAMPS 0

namespace {

constexpr int L_ = 2048, D_ = 512, FF_ = 1376, SL_ = 176;

constexpr int SLOT = 24576;
constexpr int OFF_RING = 0;
constexpr int OFF_H = 4 * SLOT;
constexpr int OFF_X16 = OFF_H;
constexpr int OFF_TR = OFF_H + 16640;
constexpr int OFF_CSR = OFF_TR + 16384;
constexpr int OFF_U = OFF_H + 45056;
constexpr int OFF_STR = OFF_U + 18432;
constexpr int STR_CH = 10304;
constexpr int OFF_TAB = OFF_STR + 4 * STR_CH;
constexpr int TAB_CH = 4224;
constexpr int TAB_FIX = 2304, TAB_Q2 = 2560, TAB_Q3 = 3584;
constexpr int OFF_CS = OFF_TAB + 4 * TAB_CH;
constexpr int OFF_STAT = OFF_CS + 11264;
constexpr int OFF_BAR = OFF_STAT + 1024;
constexpr int SMEM_BYTES = OFF_BAR + 128;
static_assert(SMEM_BYTES <= 232448, "smem");
static_assert(OFF_CSR % 128 == 0 && OFF_CSR + 11264 <= OFF_U, "alias");
enum { B_FULL = 0, B_EMPTY = 4, B_X = 8, B_CSR = 9, B_H = 10, B_S = 12, B_U = 13, B_C = 14 };

__device__ uint4 g_u[128 * 128 * 8];
__device__ float2 g_stats[L_];
__device__ float g_cs[8 * 16 * SL_];
__device__ uint4 g_part[128 * 3 * 2 * 8 * 128];
__device__ uint2 g_ao[128 * 2 * 128 * 8];
__device__ unsigned g_cntA, g_cntC[8], g_cntO[8], g_flagP[128 * 3 * 8], g_epoch[128];
#define GSTAMP(i)
#define STAMP(i)

__device__ __forceinline__ void mbar_init(uint32_t b, uint32_t n) { asm volatile("mbarrier.init.shared::cta.b64 [%0], %1;" ::"r"(b), "r"(n) : "memory"); }
__device__ __forceinline__ void mbar_expect(uint32_t b, uint32_t tx) { asm volatile("mbarrier.arrive.expect_tx.shared::cta.b64 _, [%0], %1;" ::"r"(b), "r"(tx) : "memory"); }
__device__ __forceinline__ void mbar_arrive(uint32_t b) { asm volatile("mbarrier.arrive.shared::cta.b64 _, [%0];" ::"r"(b) : "memory"); }
__device__ __forceinline__ void mbar_wait(uint32_t b, uint32_t parity) {
    uint32_t ok = 0;
#pragma unroll 1
    for (int it = 0; it < (1 << 22); it++) {
        asm volatile("{\n.reg .pred p;\nmbarrier.try_wait.parity.shared::cta.b64 p, [%1], %2;\nselp.u32 %0, 1, 0, p;\n}\n" : "=r"(ok) : "r"(b), "r"(parity) : "memory");
        if (ok) return;
    }
    __trap();
}
__device__ __forceinline__ void mbar_wait_cluster(uint32_t b, uint32_t parity) {
    uint32_t ok = 0;
#pragma unroll 1
    for (int it = 0; it < (1 << 22); it++) {
        asm volatile("{\n.reg .pred p;\nmbarrier.try_wait.parity.acquire.cluster.shared::cta.b64 p, [%1], %2;\nselp.u32 %0, 1, 0, p;\n}\n" : "=r"(ok) : "r"(b), "r"(parity) : "memory");
        if (ok) return;
    }
    __trap();
}
__device__ __forceinline__ void poll_ge(const unsigned* p, unsigned target) {
    asm volatile("{\n.reg .pred p, q;\n.reg .u32 v, i;\nmov.u32 i, 0;\nPOLL_L:\nld.acquire.gpu.global.u32 v, [%0];\nsub.u32 v, v, %1;\nsetp.lt.s32 p, v, 0;\n"
                 "add.u32 i, i, 1;\nsetp.lt.and.u32 q, i, 1048576, p;\n@q bra POLL_L;\n@p trap;\n}\n" ::"l"(p), "r"(target) : "memory");
}
__device__ __forceinline__ void post_add(unsigned* p) { asm volatile("red.release.gpu.global.add.u32 [%0], 1;" ::"l"(p) : "memory"); }
__device__ __forceinline__ void post_set(unsigned* p, unsigned v) { asm volatile("st.release.gpu.global.u32 [%0], %1;" ::"l"(p), "r"(v) : "memory"); }
__device__ __forceinline__ void bar_sync(int id, int n) { asm volatile("bar.sync %0, %1;" ::"r"(id), "r"(n) : "memory"); }
__device__ __forceinline__ uint4 lds128(uint32_t a) { uint4 v; asm volatile("ld.shared.v4.u32 {%0,%1,%2,%3}, [%4];" : "=r"(v.x), "=r"(v.y), "=r"(v.z), "=r"(v.w) : "r"(a) : "memory"); return v; }
__device__ __forceinline__ uint2 lds64(uint32_t a) { uint2 v; asm volatile("ld.shared.v2.u32 {%0,%1}, [%2];" : "=r"(v.x), "=r"(v.y) : "r"(a) : "memory"); return v; }
__device__ __forceinline__ uint32_t lds32(uint32_t a) { uint32_t v; asm volatile("ld.shared.u32 %0, [%1];" : "=r"(v) : "r"(a) : "memory"); return v; }
__device__ __forceinline__ void sts128(uint32_t a, uint32_t x, uint32_t y, uint32_t z, uint32_t w) { asm volatile("st.shared.v4.u32 [%0], {%1,%2,%3,%4};" ::"r"(a), "r"(x), "r"(y), "r"(z), "r"(w) : "memory"); }
__device__ __forceinline__ void sts64(uint32_t a, uint32_t x, uint32_t y) { asm volatile("st.shared.v2.u32 [%0], {%1,%2};" ::"r"(a), "r"(x), "r"(y) : "memory"); }
__device__ __forceinline__ void sts32(uint32_t a, uint32_t x) { asm volatile("st.shared.u32 [%0], %1;" ::"r"(a), "r"(x) : "memory"); }
__device__ __forceinline__ void ldsm4(uint32_t* r, uint32_t a) { asm volatile("ldmatrix.sync.aligned.m8n8.x4.shared.b16 {%0,%1,%2,%3}, [%4];" : "=r"(r[0]), "=r"(r[1]), "=r"(r[2]), "=r"(r[3]) : "r"(a) : "memory"); }
__device__ __forceinline__ void ldsm4t(uint32_t* r, uint32_t a) { asm volatile("ldmatrix.sync.aligned.m8n8.x4.trans.shared.b16 {%0,%1,%2,%3}, [%4];" : "=r"(r[0]), "=r"(r[1]), "=r"(r[2]), "=r"(r[3]) : "r"(a) : "memory"); }
__device__ __forceinline__ void stsm4(uint32_t a, uint32_t x, uint32_t y, uint32_t z, uint32_t w) { asm volatile("stmatrix.sync.aligned.m8n8.x4.shared.b16 [%0], {%1,%2,%3,%4};" ::"r"(a), "r"(x), "r"(y), "r"(z), "r"(w) : "memory"); }
__device__ __forceinline__ void cp16(uint32_t dst, const void* src) { asm volatile("cp.async.cg.shared.global [%0], [%1], 16;" ::"r"(dst), "l"(src) : "memory"); }
__device__ __forceinline__ void cp_wait_all() { asm volatile("cp.async.wait_all;" ::: "memory"); }
__device__ __forceinline__ uint4 ldg_nc128(const void* p) { uint4 v; asm volatile("ld.global.nc.L1::no_allocate.v4.u32 {%0,%1,%2,%3}, [%4];" : "=r"(v.x), "=r"(v.y), "=r"(v.z), "=r"(v.w) : "l"(p)); return v; }
__device__ __forceinline__ uint4 ldg_cg128(const void* p) { uint4 v; asm volatile("ld.global.cg.v4.u32 {%0,%1,%2,%3}, [%4];" : "=r"(v.x), "=r"(v.y), "=r"(v.z), "=r"(v.w) : "l"(p) : "memory"); return v; }
__device__ __forceinline__ uint2 ldg_cg64(const void* p) { uint2 v; asm volatile("ld.global.cg.v2.u32 {%0,%1}, [%2];" : "=r"(v.x), "=r"(v.y) : "l"(p) : "memory"); return v; }
__device__ __forceinline__ void stg128(void* p, uint32_t x, uint32_t y, uint32_t z, uint32_t w) { asm volatile("st.global.v4.u32 [%0], {%1,%2,%3,%4};" ::"l"(p), "r"(x), "r"(y), "r"(z), "r"(w) : "memory"); }
__device__ __forceinline__ uint32_t pack2(float lo, float hi) { uint32_t d; asm("cvt.rn.bf16x2.f32 %0, %1, %2;" : "=r"(d) : "f"(hi), "f"(lo)); return d; }
__device__ __forceinline__ uint32_t pack2relu(float lo, float hi) { uint32_t d; asm("cvt.rn.relu.bf16x2.f32 %0, %1, %2;" : "=r"(d) : "f"(hi), "f"(lo)); return d; }
__device__ __forceinline__ float blo(uint32_t v) { return __uint_as_float(v << 16); }
__device__ __forceinline__ float bhi(uint32_t v) { return __uint_as_float(v & 0xffff0000u); }
__device__ __forceinline__ float rbf(float x) { return __bfloat162float(__float2bfloat16_rn(x)); }
__device__ __forceinline__ uint32_t hsub2(uint32_t a, uint32_t b) { uint32_t d; asm("sub.rn.bf16x2 %0, %1, %2;" : "=r"(d) : "r"(a), "r"(b)); return d; }
__device__ __forceinline__ uint32_t hadd2(uint32_t a, uint32_t b) { uint32_t d; asm("add.rn.bf16x2 %0, %1, %2;" : "=r"(d) : "r"(a), "r"(b)); return d; }
__device__ __forceinline__ void mma16816(float* d, const uint32_t* a, uint32_t b0, uint32_t b1) {
    asm volatile("mma.sync.aligned.m16n8k16.row.col.f32.bf16.bf16.f32 {%0,%1,%2,%3}, {%4,%5,%6,%7}, {%8,%9}, {%0,%1,%2,%3};"
                 : "+f"(d[0]), "+f"(d[1]), "+f"(d[2]), "+f"(d[3]) : "r"(a[0]), "r"(a[1]), "r"(a[2]), "r"(a[3]), "r"(b0), "r"(b1));
}
__device__ __forceinline__ void wg_fence() { asm volatile("wgmma.fence.sync.aligned;" ::: "memory"); }
__device__ __forceinline__ void wg_commit() { asm volatile("wgmma.commit_group.sync.aligned;" ::: "memory"); }
template <int N> __device__ __forceinline__ void wg_wait() { asm volatile("wgmma.wait_group.sync.aligned %0;" ::"n"(N) : "memory"); }
#define R8(a, o) "+f"(a[o]), "+f"(a[o + 1]), "+f"(a[o + 2]), "+f"(a[o + 3]), "+f"(a[o + 4]), "+f"(a[o + 5]), "+f"(a[o + 6]), "+f"(a[o + 7])
__device__ __forceinline__ void wgmma176(float* d, uint32_t a0, uint32_t a1, uint32_t a2, uint32_t a3, uint64_t desc, int acc) {
    asm volatile("{\n.reg .pred p;\nsetp.ne.b32 p, %93, 0;\n"
                 "wgmma.mma_async.sync.aligned.m64n176k16.f32.bf16.bf16 {"
                 "%0,%1,%2,%3,%4,%5,%6,%7,%8,%9,%10,%11,%12,%13,%14,%15,%16,%17,%18,%19,%20,%21,%22,%23,%24,%25,%26,%27,%28,%29,%30,%31,"
                 "%32,%33,%34,%35,%36,%37,%38,%39,%40,%41,%42,%43,%44,%45,%46,%47,%48,%49,%50,%51,%52,%53,%54,%55,%56,%57,%58,%59,%60,%61,%62,%63,"
                 "%64,%65,%66,%67,%68,%69,%70,%71,%72,%73,%74,%75,%76,%77,%78,%79,%80,%81,%82,%83,%84,%85,%86,%87}, {%88,%89,%90,%91}, %92, p, 1, 1, 1;\n}\n"
                 : R8(d, 0), R8(d, 8), R8(d, 16), R8(d, 24), R8(d, 32), R8(d, 40), R8(d, 48), R8(d, 56), R8(d, 64), R8(d, 72), R8(d, 80)
                 : "r"(a0), "r"(a1), "r"(a2), "r"(a3), "l"(desc), "r"(acc));
}
__device__ __forceinline__ void wgmma64(float* d, const uint32_t* a, uint64_t desc, int acc) {
    asm volatile("{\n.reg .pred p;\nsetp.ne.b32 p, %37, 0;\n"
                 "wgmma.mma_async.sync.aligned.m64n64k16.f32.bf16.bf16 {"
                 "%0,%1,%2,%3,%4,%5,%6,%7,%8,%9,%10,%11,%12,%13,%14,%15,%16,%17,%18,%19,%20,%21,%22,%23,%24,%25,%26,%27,%28,%29,%30,%31"
                 "}, {%32,%33,%34,%35}, %36, p, 1, 1, 1;\n}\n"
                 : R8(d, 0), R8(d, 8), R8(d, 16), R8(d, 24)
                 : "r"(a[0]), "r"(a[1]), "r"(a[2]), "r"(a[3]), "l"(desc), "r"(acc));
}
template <int N> __device__ __forceinline__ void keep(float* a) {
#pragma unroll
    for (int i = 0; i < N; i++) asm volatile("" : "+f"(a[i])::"memory");
}
__device__ __forceinline__ void tma2d(uint32_t dst, const CUtensorMap* m, uint32_t bar, int c0, int c1) {
    asm volatile("cp.async.bulk.tensor.2d.shared::cluster.global.mbarrier::complete_tx::bytes [%0], [%1, {%3, %4}], [%2];" ::"r"(dst), "l"(m), "r"(bar), "r"(c0), "r"(c1) : "memory");
}
__device__ __forceinline__ void tma5d(uint32_t dst, const CUtensorMap* m, uint32_t bar, int c0, int c4) {
    asm volatile("cp.async.bulk.tensor.5d.shared::cluster.global.mbarrier::complete_tx::bytes [%0], [%1, {%3, %5, %5, %5, %4}], [%2];" ::"r"(dst), "l"(m), "r"(bar), "r"(c0), "r"(c4), "r"(0) : "memory");
}
__device__ __forceinline__ void bulk_g2s(uint32_t dst, const void* src, uint32_t bytes, uint32_t bar) {
    asm volatile("cp.async.bulk.shared::cluster.global.mbarrier::complete_tx::bytes [%0], [%1], %2, [%3];" ::"r"(dst), "l"(src), "r"(bytes), "r"(bar) : "memory");
}
struct cf { float x, y; };
__device__ __forceinline__ cf cmul(cf a, cf b) { cf r; r.x = fmaf(a.x, b.x, -a.y * b.y); r.y = fmaf(a.x, b.y, a.y * b.x); return r; }
__device__ __forceinline__ cf cexp_(float re, float im) {
    float mag;
    asm("ex2.approx.ftz.f32 %0, %1;" : "=f"(mag) : "f"(re * 1.4426950408889634f));
    float k = rintf(im * 0.15915494309189535f);
    float r = fmaf(k, -6.2831854820251465f, im);
    r = fmaf(k, 1.7484556000744487e-7f, r);
    cf o; o.x = mag * __cosf(r); o.y = mag * __sinf(r);
    return o;
}

struct Params {
    const __nv_bfloat16 *x, *a_re, *a_im, *b_re, *b_im, *c_re, *c_im, *log_dt, *dskip;
    __nv_bfloat16* out;
};

__device__ __forceinline__ void issue_item(int k, uint32_t sb, int s, const CUtensorMap* mw1, const CUtensorMap* mw2) {
    const uint32_t dst = sb + OFF_RING + (k & 3) * SLOT, bar = sb + OFF_BAR + 8 * (B_FULL + (k & 3));
    if (k < 8) {
        mbar_expect(bar, 24576);
#pragma unroll
        for (int a = 0; a < 3; a++) tma5d(dst + a * 8192, mw1, bar, SL_ * s + 64 * a, 2 * k);
    } else {
        const int pos = (k - 8) >> 1, hh = k & 1;
        const int chi = ((s >> 1) + 1 + pos) & 3;
        mbar_expect(bar, 22528);
        tma2d(dst, mw2, bar, 256 * (s & 1) + 64 * chi, SL_ * (s ^ hh));
    }
}

__global__ void __cluster_dims__(2, 1, 1) __launch_bounds__(512, 1)
fused_kernel(const __grid_constant__ CUtensorMap mw1, const __grid_constant__ CUtensorMap mw1c, const __grid_constant__ CUtensorMap mw2, const Params p) {
    extern __shared__ __align__(1024) unsigned char smem[];
    const uint32_t sb = (uint32_t)__cvta_generic_to_shared(smem);
    const int b = blockIdx.x, s = b & 7, mt = b >> 3;
    const int warp = threadIdx.x >> 5, lane = threadIdx.x & 31, g = lane >> 2, c = lane & 3;
    const uint32_t bars = sb + OFF_BAR;
    if (warp == 0) { STAMP(0); GSTAMP(62); }

    if (warp >= 12) {
        asm volatile("setmaxnreg.dec.sync.aligned.u32 40;");
        const int pw = warp - 12, pt = threadIdx.x - 384;
        STAMP(48 + pw);
        if (lane == 0) {
            mbar_init(bars + 8 * (B_FULL + pw), 1);
            mbar_init(bars + 8 * (B_EMPTY + pw), 8);
            if (pw == 1) mbar_init(bars + 8 * B_X, 1);
            if (pw == 2) mbar_init(bars + 8 * B_CSR, 1);
            if (pw == 3) {
                mbar_init(bars + 8 * B_H, 1); mbar_init(bars + 8 * (B_H + 1), 1);
                mbar_init(bars + 8 * B_S, 1); mbar_init(bars + 8 * B_U, 1); mbar_init(bars + 8 * B_C, 4);
            }
            asm volatile("fence.mbarrier_init.release.cluster;" ::: "memory");
            asm volatile("fence.proxy.async.shared::cta;" ::: "memory");
            if (pw == 1) mbar_expect(bars + 8 * B_X, 16384);
            if (pw == 3) { mbar_expect(bars + 8 * B_H, 22528); mbar_expect(bars + 8 * (B_H + 1), 22528); }
        }
        __syncwarp();
        if (pw == 1 && lane < 16) bulk_g2s(sb + OFF_X16 + lane * 1040, p.x + (size_t)(16 * b + lane) * D_, 1024, bars + 8 * B_X);
        if (lane == 0) {
            issue_item(pw, sb, s, &mw1, &mw2);
            if (pw == 2) { mbar_expect(bars + 8 * B_CSR, 11264); tma2d(sb + OFF_CSR, &mw1c, bars + 8 * B_CSR, SL_ * s, 32 * mt); }
        }
        const unsigned epoch = g_epoch[b] + 1;
        if (pw < 3) STAMP(28 + pw);
        bar_sync(0, 512);
        mbar_wait(bars + 8 * B_X, 0);
        STAMP(52 + pw);
        {
            const int row = 4 * pw + (lane >> 3);
            const uint32_t ra = sb + OFF_X16 + row * 1040;
            const float piv = blo(lds32(ra));
            float s1 = 0.f, s2 = 0.f;
#pragma unroll
            for (int i = 0; i < 8; i++) {
                uint4 v = lds128(ra + (8 * i + (lane & 7)) * 16);
                uint32_t w4[4] = {v.x, v.y, v.z, v.w};
#pragma unroll
                for (int j = 0; j < 4; j++) {
                    float lo = blo(w4[j]) - piv, hi = bhi(w4[j]) - piv;
                    s1 += lo; s2 = fmaf(lo, lo, s2);
                    s1 += hi; s2 = fmaf(hi, hi, s2);
                }
            }
#pragma unroll
            for (int o = 1; o < 8; o <<= 1) { s1 += __shfl_xor_sync(~0u, s1, o); s2 += __shfl_xor_sync(~0u, s2, o); }
            const float e1 = s1 * (1.f / 512.f);
            const float var = fmaxf(fmaf(-e1, e1, s2 * (1.f / 512.f)), 0.f);
            const float mb = rbf(piv + e1);
            const float sd = rbf(sqrtf(rbf(rbf(var) + 1e-5f)));
            const float rs = 1.0f / sd;
            if ((lane & 7) == 0) {
                sts64(sb + OFF_X16 + row * 1040 + 1024, __float_as_uint(mb), __float_as_uint(rs));
                g_stats[16 * b + row] = make_float2(mb, rs);
            }
        }
        bar_sync(1, 128);
        {
            uint32_t m2[2]; float rr[4];
#pragma unroll
            for (int h = 0; h < 2; h++) {
                uint2 q0 = lds64(sb + OFF_X16 + (8 * h + 2 * c) * 1040 + 1024), q1 = lds64(sb + OFF_X16 + (8 * h + 2 * c + 1) * 1040 + 1024);
                m2[h] = (q0.x >> 16) | (q1.x & 0xffff0000u);
                rr[2 * h] = __uint_as_float(q0.y); rr[2 * h + 1] = __uint_as_float(q1.y);
            }
            const int mi = lane >> 3, r7 = lane & 7;
            const uint32_t la = sb + OFF_X16 + (8 * (mi & 1) + r7) * 1040 + (128 * pw + 8 * (mi >> 1)) * 2;
            const int ch0 = 128 * pw + 8 * (mi >> 1) + r7;
            const uint32_t sa = sb + OFF_TR + (ch0 >> 2) * 128 + (((2 * (ch0 & 3) + (mi & 1)) ^ (b & 7)) << 4);
#pragma unroll 2
            for (int it = 0; it < 8; it++) {
                uint32_t r[4];
                ldsm4t(r, la + it * 32);
#pragma unroll
                for (int j = 0; j < 4; j++) {
                    uint32_t d = hsub2(r[j], m2[j & 1]);
                    r[j] = pack2(blo(d) * rr[2 * (j & 1)], bhi(d) * rr[2 * (j & 1) + 1]);
                }
                stsm4(sa + it * 512, r[0], r[1], r[2], r[3]);
            }
            __syncwarp();
#pragma unroll
            for (int i = 0; i < 8; i++) {
                const int line = 32 * pw + 4 * i + (lane >> 3);
                uint4 v = lds128(sb + OFF_TR + line * 128 + (lane & 7) * 16);
                stg128(&g_u[(line * 128 + b) * 8 + (lane & 7)], v.x, v.y, v.z, v.w);
            }
        }
        __threadfence();
        bar_sync(1, 128);
        if (pt == 0) post_add(&g_cntA);
        if (pw < 2) asm volatile("barrier.cluster.arrive.relaxed.aligned;" ::: "memory");
        STAMP(56 + pw);
        if (pw == 0) {
            if (lane == 0) {
#pragma unroll 1
                for (int k = 4; k < 16; k++) {
                    mbar_wait(bars + 8 * (B_EMPTY + (k & 3)), ((k >> 2) - 1) & 1);
                    issue_item(k, sb, s, &mw1, &mw2);
                }
            }
        } else if (pw == 1) {
            poll_ge(&g_cntA, 128u * epoch);
            STAMP(60);
#pragma unroll 8
            for (int i = 0; i < 32; i++) cp16(sb + OFF_U + 2048 + (i * 32 + lane) * 16, &g_u[b * 1024 + i * 32 + lane]);
            cp_wait_all();
            __syncwarp();
            if (lane == 0) mbar_arrive(bars + 8 * B_U);
            STAMP(61);
        } else {
            mbar_wait(bars + 8 * B_CSR, 0);
#pragma unroll 1
            for (int cp = pt - 64; cp < 88; cp += 64) {
                float a0 = 0.f, a1 = 0.f;
#pragma unroll 8
                for (int r = 0; r < 32; r++) { uint32_t v = lds32(sb + OFF_CSR + r * 352 + cp * 4); a0 += blo(v); a1 += bhi(v); }
                *(float2*)&g_cs[(s * 16 + mt) * SL_ + 2 * cp] = make_float2(a0, a1);
            }
            __syncwarp();
            asm volatile("barrier.cluster.arrive.relaxed.aligned;" ::: "memory");
            if (lane == 0) post_add(&g_cntC[s]);
            if (pw == 2) {
                poll_ge(&g_cntA, 128u * epoch);
                poll_ge(&g_cntC[s], 32u * epoch);
#pragma unroll 1
                for (int i = lane; i < 704; i += 32) cp16(sb + OFF_CS + i * 16, (const uint4*)&g_cs[s * 16 * SL_] + i);
                cp16(sb + OFF_STAT + lane * 16, (const uint4*)&g_stats[128 * mt] + lane);
                cp16(sb + OFF_STAT + 512 + lane * 16, (const uint4*)&g_stats[128 * mt] + 32 + lane);
                cp_wait_all();
                __syncwarp();
#pragma unroll 1
                for (int cp = lane; cp < 88; cp += 32) {
                    float a0 = 0.f, a1 = 0.f;
#pragma unroll 8
                    for (int r = 0; r < 16; r++) { uint2 v = lds64(sb + OFF_CS + r * 704 + cp * 8); a0 += __uint_as_float(v.x); a1 += __uint_as_float(v.y); }
                    sts64(sb + OFF_CS + cp * 8, __float_as_uint(a0), __float_as_uint(a1));
                }
                __syncwarp();
                if (lane == 0) mbar_arrive(bars + 8 * B_S);
                STAMP(31);
            }
        }
    } else if (warp >= 8) {
        asm volatile("setmaxnreg.dec.sync.aligned.u32 88;");
        const int aw = warp - 8, ch = 4 * b + aw;
        uint2 pa_re, pa_im, pb_re, pb_im, pc_re, pc_im;
        {
            const int o = ch * 32 + lane;
            pa_re = __ldg((const uint2*)p.a_re + o); pa_im = __ldg((const uint2*)p.a_im + o);
            pb_re = __ldg((const uint2*)p.b_re + o); pb_im = __ldg((const uint2*)p.b_im + o);
            pc_re = __ldg((const uint2*)p.c_re + o); pc_im = __ldg((const uint2*)p.c_im + o);
        }
        const float ldt = __bfloat162float(p.log_dt[ch]), dsk = __bfloat162float(p.dskip[ch]);
        const uint32_t stg = sb + OFF_STR + aw * STR_CH;
        sts128(sb + OFF_U + (threadIdx.x - 256) * 16, 0, 0, 0, 0);
        if (aw == 0) STAMP(15);
        bar_sync(0, 512);
        asm volatile("barrier.cluster.arrive.relaxed.aligned;" ::: "memory");
        const float dt = rbf(expf(ldt));
        float kacc[2][3][4];
#pragma unroll
        for (int i = 0; i < 24; i++) (&kacc[0][0][0])[i] = 0.f;
        STAMP(40 + aw);
#pragma unroll 1
        for (int rd = 0; rd < 4; rd++) {
            auto sel = [&](uint2 v) { uint32_t w = (rd & 2) ? v.y : v.x; return (rd & 1) ? bhi(w) : blo(w); };
            const float zr = dt * sel(pa_re), zi = dt * sel(pa_im);
            cf dB = {dt * sel(pb_re), dt * sel(pb_im)}, C = {sel(pc_re), sel(pc_im)};
            cf g0 = cmul(C, dB); g0.y = -g0.y;
            const cf w1 = cexp_(zr, -zi), H1 = cexp_(256.f * zr, -256.f * zi), w8 = cexp_(8.f * zr, 8.f * zi);
            const uint32_t fa = stg + lane * 16;
            {
                cf E[4], O[4];
                E[0].x = 1.f; E[0].y = 0.f; E[1] = w8; E[2] = cmul(w8, w8); E[3] = cmul(E[2], w8);
                const cf F4 = cmul(E[2], E[2]);
#pragma unroll
                for (int q = 0; q < 4; q++) {
#pragma unroll
                    for (int i = 0; i < 4; i++) O[i] = (q == 0 && i == 0) ? F4 : cmul(E[i], F4);
                    sts128(fa + (2 * q) * 512, pack2(E[0].x, E[1].x), pack2(E[2].x, E[3].x), pack2(O[0].x, O[1].x), pack2(O[2].x, O[3].x));
                    sts128(fa + (2 * q + 1) * 512, pack2(E[0].y, E[1].y), pack2(E[2].y, E[3].y), pack2(O[0].y, O[1].y), pack2(O[2].y, O[3].y));
                    if (q < 3) {
#pragma unroll
                        for (int i = 0; i < 4; i++) E[i] = cmul(O[i], F4);
                    }
                }
            }
            {
                cf gg[8];
                gg[0] = g0;
#pragma unroll
                for (int i = 1; i < 8; i++) gg[i] = cmul(gg[i - 1], w1);
                sts128(fa + 4096, pack2(gg[0].x, gg[1].x), pack2(gg[2].x, gg[3].x), pack2(gg[4].x, gg[5].x), pack2(gg[6].x, gg[7].x));
                sts128(fa + 4608, pack2(gg[0].y, gg[1].y), pack2(gg[2].y, gg[3].y), pack2(gg[4].y, gg[5].y), pack2(gg[6].y, gg[7].y));
                const cf H2 = cmul(H1, H1);
                const cf G8 = cmul(gg[0], H1), G9 = cmul(gg[2], H1), G10 = cmul(gg[4], H1), G11 = cmul(gg[6], H1);
                const cf G12 = cmul(gg[0], H2), G13 = cmul(gg[4], H2), G14 = cmul(G12, H1), G15 = cmul(G13, H1);
                sts128(fa + 5120, pack2(G8.x, G9.x), pack2(G10.x, G11.x), pack2(G12.x, G13.x), pack2(G14.x, G15.x));
                sts128(fa + 5632, pack2(G8.y, G9.y), pack2(G10.y, G11.y), pack2(G12.y, G13.y), pack2(G14.y, G15.y));
                const cf G16 = cmul(G12, H2), G17 = cmul(G16, H1), G18 = cmul(G16, H2), G19 = cmul(G17, H2), G20 = cmul(G18, H2);
                sts128(fa + 6144, pack2(G16.x, G17.x), pack2(G18.x, G19.x), pack2(G20.x, 0.f), 0);
                sts128(fa + 6656, pack2(G16.y, G17.y), pack2(G18.y, G19.y), pack2(G20.y, 0.f), 0);
            }
            __syncwarp();
            const int mi = lane >> 3, r7 = lane & 7;
            const uint32_t aa = stg + ((mi & 1) * 2 + (mi >> 1)) * 512 + r7 * 16;
            const uint32_t ba = stg + 4096 + (mi & 1) * 512 + ((mi >> 1) * 8 + r7) * 16;
#pragma unroll
            for (int kp = 0; kp < 2; kp++) {
                uint32_t bb[3][4];
#pragma unroll
                for (int n = 0; n < 3; n++) ldsm4t(bb[n], ba + n * 1024 + kp * 256);
#pragma unroll
                for (int kk = 0; kk < 2; kk++) {
#pragma unroll
                    for (int m = 0; m < 2; m++) {
                        uint32_t a[4];
                        ldsm4t(a, aa + m * 2048 + (2 * kp + kk) * 128);
#pragma unroll
                        for (int n = 0; n < 3; n++) mma16816(kacc[m][n], a, bb[n][2 * kk], bb[n][2 * kk + 1]);
                    }
                }
            }
            __syncwarp();
        }
        STAMP(44 + aw);
        {
            int l1[3][2];
#pragma unroll
            for (int e = 0; e < 2; e++) {
                const int n = 2 * c + e;
                l1[0][e] = n;
                l1[1][e] = n < 4 ? 256 + 2 * n : 512 + 256 * ((n - 4) >> 1) + 4 * (n & 1);
                l1[2][e] = n < 4 ? 1024 + 256 * n : 2044 + n;
            }
#pragma unroll
            for (int m = 0; m < 2; m++)
#pragma unroll
                for (int n = 0; n < 3; n++)
#pragma unroll
                    for (int i = 0; i < 4; i++) sts32(stg + (l1[n][i & 1] + 8 * (16 * m + g + 8 * (i >> 1))) * 4, __float_as_uint(kacc[m][n][i]));
        }
        __syncwarp();
        {
            const uint32_t tab = sb + OFF_TAB + aw * TAB_CH;
            auto Kt = [&](int idx) { return __uint_as_float(lds32(stg + idx * 4)); };
            auto Kex = [&](int l) { float v = 0.f; if (l >= 0 && l <= 517) { v = Kt(__float2int_rn(rbf((float)l))); if (l == 0) v += dsk; } return v; };
#pragma unroll 2
            for (int i = 0; i < 18; i++) { const int x = 32 * i + lane - 16; sts32(tab + (x + 16) * 4, pack2(Kex(x), Kex(x - 1))); }
            const float k1024 = Kt(1024);
#pragma unroll
            for (int i = 0; i < 2; i++) { const int x = 32 * i + lane - 16; sts32(tab + TAB_FIX + (x + 16) * 4, pack2((x == 3 || x == 4) ? k1024 : 0.f, (x == 4 || x == 5) ? k1024 : 0.f)); }
#pragma unroll 1
            for (int i = 0; i < 8; i++) {
                const int ss = i >> 1, x = 16 + 32 * (i & 1) + lane, off = 8 + 8 * (ss & 1) + 4 * (ss >> 1), hi = ss == 3 ? 63 : 64;
                const float t0 = (x >= 32 && x < hi) ? Kt(16 * x + off) : 0.f, t1 = (x - 1 >= 32 && x - 1 < hi) ? Kt(16 * x - 16 + off) : 0.f;
                sts32(tab + TAB_Q2 + ss * 256 + (x - 16) * 4, pack2(t0, t1));
            }
#pragma unroll 1
            for (int i = 0; i < 5; i++) {
                const int y = 32 * i + lane, ss = y >= 80, x = 48 + y - 80 * ss, off = ss ? 8 : 16;
                const float t0 = x >= 64 ? Kt(16 * x + off) : 0.f, t1 = x - 1 >= 64 ? Kt(16 * x - 16 + off) : 0.f;
                sts32(tab + TAB_Q3 + y * 4, pack2(t0, t1));
            }
        }
        __syncwarp();
        STAMP(32 + aw);
        mbar_wait(bars + 8 * B_U, 0);
        if (lane < 4) sts128(stg + lane * 16, 0, 0, 0, 0);
#pragma unroll 1
        for (int t = 0; t < 3; t++) {
            const int j = 32 * t + lane;
            const uint32_t ub = sb + OFF_U + 2048 + j * 128;
            float P[36];
            {
                uint4 v[5];
                v[0] = lds128(ub - 256 + (((2 * aw + 1) ^ ((j - 2) & 7)) << 4));
                v[1] = lds128(ub - 128 + (((2 * aw) ^ ((j - 1) & 7)) << 4));
                v[2] = lds128(ub - 128 + (((2 * aw + 1) ^ ((j - 1) & 7)) << 4));
                v[3] = lds128(ub + (((2 * aw) ^ (j & 7)) << 4));
                v[4] = lds128(ub + (((2 * aw + 1) ^ (j & 7)) << 4));
                const uint32_t* w = &v[0].x;
                P[4] = 0.f;
#pragma unroll
                for (int i = 4; i < 35; i++) P[i + 1] = P[i] + ((i & 1) ? bhi(w[i >> 1]) : blo(w[i >> 1]));
            }
            const uint32_t o1 = stg + 64 + j * 64, o2 = stg + 6208 + j * 64;
            const int sw = (j >> 1) & 3;
#pragma unroll
            for (int h = 0; h < 2; h++) {
                const int q = 8 * h;
                sts128(o1 + ((h ^ sw) << 4), pack2(P[q + 19] - P[q + 14], P[q + 20] - P[q + 15]), pack2(P[q + 21] - P[q + 16], P[q + 22] - P[q + 17]),
                       pack2(P[q + 23] - P[q + 18], P[q + 24] - P[q + 19]), pack2(P[q + 25] - P[q + 20], P[q + 26] - P[q + 21]));
                sts128(o1 + (((2 + h) ^ sw) << 4), pack2(P[q + 14] - P[q + 11], P[q + 15] - P[q + 12]), pack2(P[q + 16] - P[q + 13], P[q + 17] - P[q + 14]),
                       pack2(P[q + 18] - P[q + 15], P[q + 19] - P[q + 16]), pack2(P[q + 20] - P[q + 17], P[q + 21] - P[q + 18]));
                if (t < 2) {
                    sts128(o2 + ((h ^ sw) << 4), pack2(P[q + 13] - P[q + 4], P[q + 14] - P[q + 5]), pack2(P[q + 15] - P[q + 6], P[q + 16] - P[q + 7]),
                           pack2(P[q + 17] - P[q + 8], P[q + 18] - P[q + 9]), pack2(P[q + 19] - P[q + 10], P[q + 20] - P[q + 11]));
                    sts128(o2 + (((2 + h) ^ sw) << 4), pack2(P[q + 20] - P[q + 13], P[q + 21] - P[q + 14]), pack2(P[q + 22] - P[q + 15], P[q + 23] - P[q + 16]),
                           pack2(P[q + 24] - P[q + 17], P[q + 25] - P[q + 18]), pack2(P[q + 26] - P[q + 19], P[q + 27] - P[q + 20]));
                }
            }
        }
        __syncwarp();
        if (lane == 0) mbar_arrive(bars + 8 * B_C);
        STAMP(36 + aw);
    } else {
        asm volatile("setmaxnreg.inc.sync.aligned.u32 192;");
        const int wg = warp >> 2, w = warp & 3, tid = threadIdx.x;
        const int rloc = 64 * wg + 16 * w + g;
        const uint64_t dhi = ((uint64_t)1 << 62) | ((uint64_t)(1024 >> 4) << 32) | ((uint64_t)(8192 >> 4) << 16) | (((sb + OFF_RING) & 0x3ffffu) >> 4);
        uint32_t hown[44], hpeer[44];
        if (warp == 0) STAMP(13);
        {
            const __nv_bfloat16* xp = p.x + (size_t)(128 * mt + rloc) * D_ + 8 * c;
            uint4 xr[4][2][2];
#pragma unroll
            for (int G = 0; G < 4; G++)
#pragma unroll
                for (int i = 0; i < 2; i++) { xr[G][i][0] = ldg_nc128(xp + 64 * G + 32 * i); xr[G][i][1] = ldg_nc128(xp + 8 * D_ + 64 * G + 32 * i); }
            if (warp == 0) STAMP(14);
            bar_sync(0, 512);
            asm volatile("barrier.cluster.arrive.relaxed.aligned;" ::: "memory");
            float acc[88];
#pragma unroll
            for (int st = 0; st < 8; st++) {
                mbar_wait(bars + 8 * (B_FULL + (st & 3)), (st >> 2) & 1);
                if (warp == 0 && (st == 0 || st == 4)) STAMP(1 + (st >> 2));
                const uint64_t desc = dhi + (st & 3) * (SLOT >> 4);
                wg_fence();
#pragma unroll
                for (int kk = 0; kk < 4; kk++) {
                    const uint4 R = xr[st & 3][kk >> 1][0], S = xr[st & 3][kk >> 1][1];
                    if (kk & 1) wgmma176(acc, R.z, S.z, R.w, S.w, desc + kk * 128, 1);
                    else wgmma176(acc, R.x, S.x, R.y, S.y, desc + kk * 128, (st | kk) != 0);
                }
                wg_commit();
                if (st > 0) {
                    wg_wait<1>();
                    if (lane == 0) mbar_arrive(bars + 8 * (B_EMPTY + ((st - 1) & 3)));
                    if (st + 3 < 8) {
#pragma unroll
                        for (int i = 0; i < 2; i++) { xr[(st - 1) & 3][i][0] = ldg_nc128(xp + 64 * (st + 3) + 32 * i); xr[(st - 1) & 3][i][1] = ldg_nc128(xp + 8 * D_ + 64 * (st + 3) + 32 * i); }
                    }
                }
            }
            wg_wait<0>();
            keep<88>(acc);
            if (lane == 0) mbar_arrive(bars + 8 * (B_EMPTY + 3));
            if (w == 0) STAMP(3 + wg);
            mbar_wait(bars + 8 * B_S, 0);
            const float m0 = -__uint_as_float(lds32(sb + OFF_STAT + rloc * 8)), m1 = -__uint_as_float(lds32(sb + OFF_STAT + (rloc + 8) * 8));
#pragma unroll
            for (int j = 0; j < 22; j++) {
                const uint2 q = lds64(sb + OFF_CS + (8 * j + 2 * c) * 4);
                const float c0 = __uint_as_float(q.x), c1 = __uint_as_float(q.y);
                hown[2 * j] = pack2relu(fmaf(m0, c0, acc[4 * j]), fmaf(m0, c1, acc[4 * j + 1]));
                hown[2 * j + 1] = pack2relu(fmaf(m1, c0, acc[4 * j + 2]), fmaf(m1, c1, acc[4 * j + 3]));
            }
            asm volatile("barrier.cluster.wait.acquire.aligned;" ::: "memory");
            uint32_t rdst, rbar;
            asm("mapa.shared::cluster.u32 %0, %1, %2;" : "=r"(rdst) : "r"(sb + OFF_H + tid * 16), "r"((b & 1) ^ 1));
            asm("mapa.shared::cluster.u32 %0, %1, %2;" : "=r"(rbar) : "r"(bars + 8 * (B_H + wg)), "r"((b & 1) ^ 1));
#pragma unroll
            for (int k = 0; k < 11; k++)
                asm volatile("st.async.weak.shared::cluster.mbarrier::complete_tx::bytes.v4.b32 [%0], {%1,%2,%3,%4}, [%5];" ::"r"(rdst + k * 4096),
                             "r"(hown[4 * k]), "r"(hown[4 * k + 1]), "r"(hown[4 * k + 2]), "r"(hown[4 * k + 3]), "r"(rbar) : "memory");
        }
        const unsigned epoch = g_epoch[b] + 1;
        if (w == 0) STAMP(5 + wg);
        {
            const int chl = 2 * wg + (w >> 1), par = w & 1;
            const uint32_t tab = sb + OFF_TAB + chl * TAB_CH, str = sb + OFF_STR + chl * STR_CH;
            const int mi = lane >> 3, r7 = lane & 7;
            float y[8][4];
#pragma unroll
            for (int i = 0; i < 32; i++) (&y[0][0])[i] = 0.f;
            mbar_wait(bars + 8 * B_C, 0);
            if (w == 0) STAMP(7 + wg);
            const uint32_t ta = tab + (16 + g - 2 * c) * 4;
#pragma unroll 1
            for (int dl = 0; dl < 8; dl++) {
                uint32_t A[4][4];
#pragma unroll
                for (int om = 0; om < 4; om++) {
                    const uint32_t a = ta + (128 * om + 16 * dl) * 4;
                    A[om][0] = lds32(a); A[om][1] = lds32(a + 32); A[om][2] = lds32(a - 32); A[om][3] = A[om][0];
                }
                const uint32_t ua = sb + OFF_U + 2048 + (8 * (par - 1 + (mi >> 1)) + r7 - dl) * 128 + (((2 * chl + (mi & 1)) ^ ((r7 - dl) & 7)) << 4);
#pragma unroll
                for (int mp = 0; mp < 8; mp++) {
                    uint32_t B[4];
                    ldsm4(B, ua + mp * 2048);
                    mma16816(y[mp], A[1], B[0], B[1]);
                    if (mp + 1 < 8) mma16816(y[mp + 1], A[3], B[0], B[1]);
                    mma16816(y[mp], A[0], B[2], B[3]);
                    if (mp + 1 < 8) mma16816(y[mp + 1], A[2], B[2], B[3]);
                }
            }
#pragma unroll 1
            for (int dl = 0; dl < 2; dl++) {
                uint32_t A4[4], A8[4];
                const uint32_t a = ta + (512 + 16 * dl) * 4, f = ta + TAB_FIX + 16 * dl * 4;
                A4[0] = lds32(a); A4[1] = lds32(a + 32); A4[2] = lds32(a - 32); A4[3] = A4[0];
                A8[0] = lds32(f); A8[1] = lds32(f + 32); A8[2] = lds32(f - 32); A8[3] = A8[0];
                const uint32_t ua = sb + OFF_U + 2048 + (8 * (par + 2 * (mi >> 1)) + r7 - dl) * 128 + (((2 * chl + (mi & 1)) ^ ((r7 - dl) & 7)) << 4);
#pragma unroll
                for (int mp = 0; mp < 3; mp++) {
                    uint32_t B[4];
                    ldsm4(B, ua + mp * 4096);
                    mma16816(y[2 * mp + 2], A4, B[0], B[1]);
                    mma16816(y[2 * mp + 3], A4, B[2], B[3]);
                    if (mp < 2) { mma16816(y[2 * mp + 4], A8, B[0], B[1]); mma16816(y[2 * mp + 5], A8, B[2], B[3]); }
                }
            }
#pragma unroll 1
            for (int ss = 0; ss < 4; ss++) {
                uint32_t Q[6];
                const uint32_t qa = tab + TAB_Q2 + ss * 256 + (8 * (par + 4) + g - 2 * c - 16) * 4;
#pragma unroll
                for (int i = 0; i < 3; i++) { Q[2 * i] = lds32(qa + 64 * i); Q[2 * i + 1] = lds32(qa + 64 * i - 32); }
                const int sh = ss & 1, hq = mi & 1;
                const int blk = 8 * (mi >> 1) + r7 - (sh & (hq ^ 1));
                const uint32_t za = str + 64 + blk * 64 + (((2 * (ss >> 1) + (hq ^ sh)) ^ ((blk >> 1) & 3)) << 4);
#pragma unroll
                for (int k = 0; k < 6; k++) {
                    uint32_t A[4];
                    ldsm4t(A, za + k * 1024);
                    mma16816(y[k + 2], A, Q[0], Q[1]);
                    if (k + 3 < 8) mma16816(y[k + 3], A, Q[2], Q[3]);
                    if (k + 4 < 8) mma16816(y[k + 4], A, Q[4], Q[5]);
                }
            }
#pragma unroll 1
            for (int ss = 0; ss < 2; ss++) {
                uint32_t Q[8];
                const uint32_t qa = tab + TAB_Q3 + ss * 320 + (8 * (par + 8) + g - 2 * c - 48) * 4;
#pragma unroll
                for (int i = 0; i < 4; i++) { Q[2 * i] = lds32(qa + 64 * i); Q[2 * i + 1] = lds32(qa + 64 * i - 32); }
                const int blk = 8 * (mi >> 1) + r7;
                const uint32_t za = str + 6208 + blk * 64 + (((2 * ss + (mi & 1)) ^ ((blk >> 1) & 3)) << 4);
#pragma unroll
                for (int k = 0; k < 4; k++) {
                    uint32_t A[4];
                    ldsm4t(A, za + k * 1024);
#pragma unroll
                    for (int i = 0; i < 4; i++)
                        if (4 + i + k < 8) mma16816(y[4 + i + k], A, Q[2 * i], Q[2 * i + 1]);
                }
            }
            if (w == 0) STAMP(9 + wg);
            bar_sync(2 + wg, 128);
            const uint32_t ao = sb + OFF_STR + 2 * wg * STR_CH;
#pragma unroll
            for (int t = 0; t < 8; t++)
#pragma unroll
                for (int e = 0; e < 2; e++) {
                    const int a = 16 * t + 8 * par + 2 * c + e;
                    const int word = ((a * 8 + g) * 2 + (w >> 1)) ^ ((c & 1) << 4) ^ (c >> 1);
                    sts32(ao + word * 4, pack2(y[t][e], y[t][2 + e]));
                }
            bar_sync(2 + wg, 128);
#pragma unroll
            for (int i = 0; i < 4; i++) {
                const int ci = (tid & 127) + 128 * i, a = ci >> 2;
                uint4 v = lds128(ao + ((ci ^ (((a >> 1) & 1) << 2)) << 4));
                if ((a >> 2) & 1) { uint32_t t0 = v.x; v.x = v.y; v.y = t0; t0 = v.z; v.z = v.w; v.w = t0; }
                stg128((uint4*)&g_ao[(b * 2 + wg) * 1024] + ci, v.x, v.y, v.z, v.w);
            }
            __syncwarp();
            if (lane == 0) post_add(&g_cntO[b >> 4]);
            if (w == 0) STAMP(11 + wg);
        }
        {
            float acc[2][32];
            uint4 xres[4];
            uint2 aov[8];
            const int P = s >> 1, hf = s & 1;
            const uint4* pin = &g_part[(b * 3 * 2 + wg) * 1024 + (tid & 127)];
#pragma unroll
            for (int pos = 0; pos < 4; pos++) {
                float* ac = acc[pos & 1];
                float* ap = acc[(pos & 1) ^ 1];
                const int k0 = 8 + 2 * pos;
                mbar_wait(bars + 8 * (B_FULL + (k0 & 3)), (k0 >> 2) & 1);
                if (warp == 0) STAMP(16 + 2 * pos);
                {
                    const uint64_t desc = dhi + (k0 & 3) * (SLOT >> 4);
                    wg_fence();
#pragma unroll
                    for (int k = 0; k < 11; k++) wgmma64(ac, &hown[4 * k], desc + k * 128, k != 0 || pos == 3);
                    wg_commit();
                }
                if (pos == 0) {
                    mbar_wait_cluster(bars + 8 * (B_H + wg), 0);
#pragma unroll
                    for (int k = 0; k < 11; k++) {
                        uint4 v = lds128(sb + OFF_H + (k * 256 + tid) * 16);
                        hpeer[4 * k] = v.x; hpeer[4 * k + 1] = v.y; hpeer[4 * k + 2] = v.z; hpeer[4 * k + 3] = v.w;
                    }
                } else {
                    wg_wait<1>();
                    keep<32>(ap);
                    if (pos < 3 && lane == 0) mbar_arrive(bars + 8 * (B_EMPTY + ((k0 - 1) & 3)));
                    const int dest = (b & ~7) + 2 * ((P + pos) & 3) + hf;
                    uint4* po = &g_part[((dest * 3 + pos - 1) * 2 + wg) * 1024 + (tid & 127)];
#pragma unroll
                    for (int i = 0; i < 8; i++)
                        stg128(po + i * 128, __float_as_uint(ap[4 * i]), __float_as_uint(ap[4 * i + 1]), __float_as_uint(ap[4 * i + 2]), __float_as_uint(ap[4 * i + 3]));
                    __syncwarp();
                    if (lane == 0) post_set(&g_flagP[(dest * 3 + pos - 1) * 8 + warp], epoch);
                }
                mbar_wait(bars + 8 * (B_FULL + ((k0 + 1) & 3)), ((k0 + 1) >> 2) & 1);
                if (warp == 0) STAMP(17 + 2 * pos);
                {
                    const uint64_t desc = dhi + ((k0 + 1) & 3) * (SLOT >> 4);
                    wg_fence();
#pragma unroll
                    for (int k = 0; k < 11; k++) wgmma64(ac, &hpeer[4 * k], desc + k * 128, 1);
                    wg_commit();
                }
                if (pos < 2) {
                    wg_wait<1>();
                    if (lane == 0) mbar_arrive(bars + 8 * (B_EMPTY + (k0 & 3)));
                }
                if (pos == 2) {
                    poll_ge(&g_flagP[(b * 3 + 0) * 8 + warp], epoch);
#pragma unroll
                    for (int i = 0; i < 8; i++) {
                        uint4 v = ldg_cg128(pin + i * 128);
                        ap[4 * i] = __uint_as_float(v.x); ap[4 * i + 1] = __uint_as_float(v.y); ap[4 * i + 2] = __uint_as_float(v.z); ap[4 * i + 3] = __uint_as_float(v.w);
                    }
                }
            }
            float* ac = acc[1];
            float* ap = acc[0];
            poll_ge(&g_flagP[(b * 3 + 1) * 8 + warp], epoch);
#pragma unroll
            for (int i = 0; i < 8; i++) {
                uint4 v = ldg_cg128(pin + 2048 + i * 128);
                ap[4 * i] = __uint_as_float(v.x); ap[4 * i + 1] = __uint_as_float(v.y); ap[4 * i + 2] = __uint_as_float(v.z); ap[4 * i + 3] = __uint_as_float(v.w);
            }
            wg_wait<1>();
            {
                const __nv_bfloat16* xq = p.x + (size_t)(128 * mt + 64 * wg + 16 * w + (lane >> 3)) * D_ + 256 * hf + 64 * P + 8 * (lane & 7);
#pragma unroll
                for (int i = 0; i < 4; i++) xres[i] = ldg_nc128(xq + 4 * i * D_);
            }
            poll_ge(&g_cntO[4 * hf + P], 128u * epoch);
            if (warp == 0) STAMP(24);
            {
                const uint2* aq = &g_ao[((16 * (4 * hf + P) + (c >> 1)) * 2 + (c & 1)) * 1024 + (8 * mt + 4 * wg + w) * 8 + g];
#pragma unroll
                for (int j = 0; j < 8; j++) aov[j] = ldg_cg64(aq + j * 4096);
            }
            poll_ge(&g_flagP[(b * 3 + 2) * 8 + warp], epoch);
            if (warp == 0) STAMP(25);
#pragma unroll
            for (int hh = 0; hh < 2; hh++) {
                uint4 v[4];
#pragma unroll
                for (int i = 0; i < 4; i++) v[i] = ldg_cg128(pin + 4096 + (4 * hh + i) * 128);
#pragma unroll
                for (int i = 0; i < 4; i++) {
                    float* q = ap + 16 * hh + 4 * i;
                    q[0] += __uint_as_float(v[i].x); q[1] += __uint_as_float(v[i].y); q[2] += __uint_as_float(v[i].z); q[3] += __uint_as_float(v[i].w);
                }
            }
            const float r0 = __uint_as_float(lds32(sb + OFF_STAT + rloc * 8 + 4)), r1 = __uint_as_float(lds32(sb + OFF_STAT + (rloc + 8) * 8 + 4));
            wg_wait<0>();
            keep<32>(ac);
            if (warp == 0) STAMP(26);
            const uint32_t os = sb + OFF_STR + 2 * wg * STR_CH + 8192 + w * 2048;
            const int mi = lane >> 3, r7 = lane & 7;
#pragma unroll
            for (int jj = 0; jj < 4; jj++) {
                uint32_t o[4];
#pragma unroll
                for (int t = 0; t < 2; t++) {
                    const int j = 2 * jj + t;
                    o[2 * t] = pack2(fmaf(ac[4 * j] + ap[4 * j], r0, blo(aov[j].x)), fmaf(ac[4 * j + 1] + ap[4 * j + 1], r0, blo(aov[j].y)));
                    o[2 * t + 1] = pack2(fmaf(ac[4 * j + 2] + ap[4 * j + 2], r1, bhi(aov[j].x)), fmaf(ac[4 * j + 3] + ap[4 * j + 3], r1, bhi(aov[j].y)));
                }
                stsm4(os + (8 * (mi & 1) + r7) * 128 + (((2 * jj + (mi >> 1)) ^ r7) << 4), o[0], o[1], o[2], o[3]);
            }
            __syncwarp();
            __nv_bfloat16* oq = p.out + (size_t)(128 * mt + 64 * wg + 16 * w + (lane >> 3)) * D_ + 256 * hf + 64 * P + 8 * (lane & 7);
#pragma unroll
            for (int i = 0; i < 4; i++) {
                const int row = 4 * i + (lane >> 3);
                uint4 v = lds128(os + row * 128 + (((lane & 7) ^ (row & 7)) << 4));
                stg128(oq + 4 * i * D_, hadd2(v.x, xres[i].x), hadd2(v.y, xres[i].y), hadd2(v.z, xres[i].z), hadd2(v.w, xres[i].w));
            }
            if (tid == 0) g_epoch[b] = epoch;
            if (warp == 0) { STAMP(27); GSTAMP(63); }
        }
    }
}

typedef CUresult (*EncodeFn)(CUtensorMap*, CUtensorMapDataType, cuuint32_t, void*, const cuuint64_t*, const cuuint64_t*, const cuuint32_t*, const cuuint32_t*,
                             CUtensorMapInterleave, CUtensorMapSwizzle, CUtensorMapL2promotion, CUtensorMapFloatOOBfill);

}

extern "C" void kernel_launch(void* const* d_in, const int* in_sizes, int n_in, void* d_out, int out_size) {
    static EncodeFn enc = nullptr;
    if (!enc) {
        void* fn = nullptr;
        cudaDriverEntryPointQueryResult qr;
        cudaGetDriverEntryPoint("cuTensorMapEncodeTiled", &fn, cudaEnableDefault, &qr);
        enc = (EncodeFn)fn;
        cudaFuncSetAttribute(fused_kernel, cudaFuncAttributeMaxDynamicSharedMemorySize, SMEM_BYTES);
    }
    CUtensorMap mw1, mw1c, mw2;
    {
        const cuuint64_t rp = FF_ * 2;
        cuuint64_t dims[5] = {FF_, 2, 4, 4, 16};
        cuuint64_t str[4] = {rp, 8 * rp, 2 * rp, 32 * rp};
        cuuint32_t box[5] = {64, 2, 4, 4, 2}, es[5] = {1, 1, 1, 1, 1};
        enc(&mw1, CU_TENSOR_MAP_DATA_TYPE_BFLOAT16, 5, d_in[10], dims, str, box, es, CU_TENSOR_MAP_INTERLEAVE_NONE, CU_TENSOR_MAP_SWIZZLE_128B,
            CU_TENSOR_MAP_L2_PROMOTION_L2_128B, CU_TENSOR_MAP_FLOAT_OOB_FILL_NONE);
        cuuint64_t d2[2] = {FF_, D_}, s2[1] = {rp};
        cuuint32_t b2[2] = {SL_, 32};
        enc(&mw1c, CU_TENSOR_MAP_DATA_TYPE_BFLOAT16, 2, d_in[10], d2, s2, b2, es, CU_TENSOR_MAP_INTERLEAVE_NONE, CU_TENSOR_MAP_SWIZZLE_NONE,
            CU_TENSOR_MAP_L2_PROMOTION_L2_128B, CU_TENSOR_MAP_FLOAT_OOB_FILL_NONE);
        cuuint64_t d3[2] = {D_, FF_}, s3[1] = {D_ * 2};
        cuuint32_t b3[2] = {64, SL_};
        enc(&mw2, CU_TENSOR_MAP_DATA_TYPE_BFLOAT16, 2, d_in[11], d3, s3, b3, es, CU_TENSOR_MAP_INTERLEAVE_NONE, CU_TENSOR_MAP_SWIZZLE_128B,
            CU_TENSOR_MAP_L2_PROMOTION_L2_128B, CU_TENSOR_MAP_FLOAT_OOB_FILL_NONE);
    }
    Params p;
    p.x = (const __nv_bfloat16*)d_in[0];
    p.a_re = (const __nv_bfloat16*)d_in[1]; p.a_im = (const __nv_bfloat16*)d_in[2];
    p.b_re = (const __nv_bfloat16*)d_in[3]; p.b_im = (const __nv_bfloat16*)d_in[4];
    p.c_re = (const __nv_bfloat16*)d_in[5]; p.c_im = (const __nv_bfloat16*)d_in[6];
    p.log_dt = (const __nv_bfloat16*)d_in[7]; p.dskip = (const __nv_bfloat16*)d_in[8];
    p.out = (__nv_bfloat16*)d_out;
    fused_kernel<<<128, 512, SMEM_BYTES, cudaStreamPerThread>>>(mw1, mw1c, mw2, p);
}
```

```cpp
#include <cuda_runtime.h>
#include <cuda_bf16.h>
#include <cuda.h>
#include <stdint.h>

#define STAMPS 0

namespace {

constexpr int L_ = 2048, D_ = 512, FF_ = 1376, SL_ = 176;

constexpr int SLOT = 24576;
constexpr int OFF_RING = 0;
constexpr int OFF_H = 4 * SLOT;
constexpr int OFF_U = OFF_H + 49152;
constexpr int OFF_U0 = OFF_U + 1024;
constexpr int OFF_STR = OFF_U + 17408;
constexpr int STR_CH = 10304;
constexpr int OFF_TAB = OFF_STR + 4 * STR_CH;
constexpr int TAB_CH = 4224;
constexpr int TAB_FIX = 2304, TAB_Q2 = 2560, TAB_Q3 = 3584;
constexpr int OFF_CS = OFF_TAB + 4 * TAB_CH;
constexpr int OFF_STAT = OFF_CS + 2816;
constexpr int OFF_ONE = OFF_STAT + 1024;
constexpr int OFF_CNT = OFF_ONE + 128;
constexpr int OFF_BAR = OFF_CNT + 128;
constexpr int SMEM_BYTES = OFF_BAR + 256;
static_assert(SMEM_BYTES <= 232448, "smem");
static_assert(OFF_STR % 128 == 0 && OFF_TAB % 128 == 0 && OFF_CS % 128 == 0 && OFF_U0 % 1024 == 0, "align");
enum { B_FULL = 0, B_H = 4, B_T = 6, B_C = 10, B_LN = 14, B_S = 15, B_U = 16, B_KG = 17, B_KT = 21, B_KF = 23, B_Y = 25, B_N = 26 };

__device__ uint4 g_u[128 * 128 * 8];
__device__ uint2 g_stats[L_];
__device__ uint2 g_cs[8 * 16 * 96];
__device__ uint4 g_part[128 * 3 * 2 * 4 * 128];
__device__ uint4 g_ao[128 * 128 * 8];
__device__ unsigned g_epoch[128];
#define GSTAMP(i)
#define STAMP(i)

#define FAIL(code) __trap()
#define GFAIL(code) __trap()
#define PTRAP "@p trap;\n"
__device__ __forceinline__ void mbar_init(uint32_t b, uint32_t n) { asm volatile("mbarrier.init.shared::cta.b64 [%0], %1;" ::"r"(b), "r"(n) : "memory"); }
__device__ __forceinline__ void mbar_expect(uint32_t b, uint32_t tx) { asm volatile("mbarrier.arrive.expect_tx.shared::cta.b64 _, [%0], %1;" ::"r"(b), "r"(tx) : "memory"); }
__device__ __forceinline__ void mbar_arrive(uint32_t b) { asm volatile("mbarrier.arrive.shared::cta.b64 _, [%0];" ::"r"(b) : "memory"); }
__device__ __forceinline__ void mbar_wait(uint32_t b, uint32_t parity) {
    uint32_t ok = 0;
#pragma unroll 1
    for (int it = 0; it < (1 << 18); it++) {
        asm volatile("{\n.reg .pred p;\nmbarrier.try_wait.parity.shared::cta.b64 p, [%1], %2;\nselp.u32 %0, 1, 0, p;\n}\n" : "=r"(ok) : "r"(b), "r"(parity) : "memory");
        if (ok) return;
    }
    FAIL(1000 + ((b & 255) >> 3) * 2 + parity);
}
__device__ __forceinline__ void mbar_wait_cluster(uint32_t b, uint32_t parity) {
    uint32_t ok = 0;
#pragma unroll 1
    for (int it = 0; it < (1 << 18); it++) {
        asm volatile("{\n.reg .pred p;\nmbarrier.try_wait.parity.acquire.cluster.shared::cta.b64 p, [%1], %2;\nselp.u32 %0, 1, 0, p;\n}\n" : "=r"(ok) : "r"(b), "r"(parity) : "memory");
        if (ok) return;
    }
    FAIL(1000 + ((b & 255) >> 3) * 2 + parity);
}
template <int SA, int SB>
__device__ __forceinline__ void poll8(uint32_t* a, uint32_t* c, const void* pa, const void* pc, uint32_t tag) {
    asm volatile("{\n.reg .pred p, q;\n.reg .u32 t, u, i;\nmov.u32 i, 0;\nPOLL_L:\n"
                 "ld.relaxed.gpu.global.v4.u32 {%0,%1,%2,%3}, [%32];\n"
                 "ld.relaxed.gpu.global.v4.u32 {%4,%5,%6,%7}, [%32+%35];\n"
                 "ld.relaxed.gpu.global.v4.u32 {%8,%9,%10,%11}, [%32+%36];\n"
                 "ld.relaxed.gpu.global.v4.u32 {%12,%13,%14,%15}, [%32+%37];\n"
                 "ld.relaxed.gpu.global.v4.u32 {%16,%17,%18,%19}, [%33];\n"
                 "ld.relaxed.gpu.global.v4.u32 {%20,%21,%22,%23}, [%33+%38];\n"
                 "ld.relaxed.gpu.global.v4.u32 {%24,%25,%26,%27}, [%33+%39];\n"
                 "ld.relaxed.gpu.global.v4.u32 {%28,%29,%30,%31}, [%33+%40];\n"
                 "xor.b32 t, %0, %34;\nxor.b32 u, %4, %34;\nor.b32 t, t, u;\nxor.b32 u, %8, %34;\nor.b32 t, t, u;\nxor.b32 u, %12, %34;\nor.b32 t, t, u;\n"
                 "xor.b32 u, %16, %34;\nor.b32 t, t, u;\nxor.b32 u, %20, %34;\nor.b32 t, t, u;\nxor.b32 u, %24, %34;\nor.b32 t, t, u;\nxor.b32 u, %28, %34;\nor.b32 t, t, u;\n"
                 "and.b32 t, t, 1;\nsetp.ne.u32 p, t, 0;\nvote.sync.any.pred p, p, 0xffffffff;\n"
                 "add.u32 i, i, 1;\nsetp.lt.and.u32 q, i, 1048576, p;\n@q bra POLL_L;\n" PTRAP "}\n"
                 : "=r"(a[0]), "=r"(a[1]), "=r"(a[2]), "=r"(a[3]), "=r"(a[4]), "=r"(a[5]), "=r"(a[6]), "=r"(a[7]),
                   "=r"(a[8]), "=r"(a[9]), "=r"(a[10]), "=r"(a[11]), "=r"(a[12]), "=r"(a[13]), "=r"(a[14]), "=r"(a[15]),
                   "=r"(c[0]), "=r"(c[1]), "=r"(c[2]), "=r"(c[3]), "=r"(c[4]), "=r"(c[5]), "=r"(c[6]), "=r"(c[7]),
                   "=r"(c[8]), "=r"(c[9]), "=r"(c[10]), "=r"(c[11]), "=r"(c[12]), "=r"(c[13]), "=r"(c[14]), "=r"(c[15])
                 : "l"(pa), "l"(pc), "r"(tag), "n"(SA), "n"(2 * SA), "n"(3 * SA), "n"(SB), "n"(2 * SB), "n"(3 * SB) : "memory");
}
__device__ __forceinline__ void bar_sync(int id, int n) { asm volatile("bar.sync %0, %1;" ::"r"(id), "r"(n) : "memory"); }
__device__ __forceinline__ void bar_arrive(int id, int n) { asm volatile("bar.arrive %0, %1;" ::"r"(id), "r"(n) : "memory"); }
__device__ __forceinline__ float ldg_bf(const __nv_bfloat16* p) { unsigned short v; asm volatile("ld.global.nc.u16 %0, [%1];" : "=h"(v) : "l"(p)); return __uint_as_float((uint32_t)v << 16); }
__device__ __forceinline__ uint4 lds128(uint32_t a) { uint4 v; asm volatile("ld.shared.v4.u32 {%0,%1,%2,%3}, [%4];" : "=r"(v.x), "=r"(v.y), "=r"(v.z), "=r"(v.w) : "r"(a) : "memory"); return v; }
__device__ __forceinline__ uint2 lds64(uint32_t a) { uint2 v; asm volatile("ld.shared.v2.u32 {%0,%1}, [%2];" : "=r"(v.x), "=r"(v.y) : "r"(a) : "memory"); return v; }
__device__ __forceinline__ uint32_t lds32(uint32_t a) { uint32_t v; asm volatile("ld.shared.u32 %0, [%1];" : "=r"(v) : "r"(a) : "memory"); return v; }
__device__ __forceinline__ void sts128(uint32_t a, uint32_t x, uint32_t y, uint32_t z, uint32_t w) { asm volatile("st.shared.v4.u32 [%0], {%1,%2,%3,%4};" ::"r"(a), "r"(x), "r"(y), "r"(z), "r"(w) : "memory"); }
__device__ __forceinline__ void sts64(uint32_t a, uint32_t x, uint32_t y) { asm volatile("st.shared.v2.u32 [%0], {%1,%2};" ::"r"(a), "r"(x), "r"(y) : "memory"); }
__device__ __forceinline__ void sts32(uint32_t a, uint32_t x) { asm volatile("st.shared.u32 [%0], %1;" ::"r"(a), "r"(x) : "memory"); }
__device__ __forceinline__ void ldsm4(uint32_t* r, uint32_t a) { asm volatile("ldmatrix.sync.aligned.m8n8.x4.shared.b16 {%0,%1,%2,%3}, [%4];" : "=r"(r[0]), "=r"(r[1]), "=r"(r[2]), "=r"(r[3]) : "r"(a) : "memory"); }
__device__ __forceinline__ void ldsm4t(uint32_t* r, uint32_t a) { asm volatile("ldmatrix.sync.aligned.m8n8.x4.trans.shared.b16 {%0,%1,%2,%3}, [%4];" : "=r"(r[0]), "=r"(r[1]), "=r"(r[2]), "=r"(r[3]) : "r"(a) : "memory"); }
__device__ __forceinline__ void stsm4(uint32_t a, uint32_t x, uint32_t y, uint32_t z, uint32_t w) { asm volatile("stmatrix.sync.aligned.m8n8.x4.shared.b16 [%0], {%1,%2,%3,%4};" ::"r"(a), "r"(x), "r"(y), "r"(z), "r"(w) : "memory"); }
__device__ __forceinline__ uint4 ldg_nc128(const void* p) { uint4 v; asm volatile("ld.global.nc.L1::no_allocate.v4.u32 {%0,%1,%2,%3}, [%4];" : "=r"(v.x), "=r"(v.y), "=r"(v.z), "=r"(v.w) : "l"(p)); return v; }
__device__ __forceinline__ uint4 ld_rlx128(const void* p) { uint4 v; asm volatile("ld.relaxed.gpu.global.v4.u32 {%0,%1,%2,%3}, [%4];" : "=r"(v.x), "=r"(v.y), "=r"(v.z), "=r"(v.w) : "l"(p) : "memory"); return v; }
template <int N, int S> struct LdSeq {
    static __device__ __forceinline__ void v4(uint4* v, const void* p) {
        LdSeq<N - 1, S>::v4(v, p);
        asm volatile("ld.relaxed.gpu.global.v4.u32 {%0,%1,%2,%3}, [%4+%5];" : "=r"(v[N - 1].x), "=r"(v[N - 1].y), "=r"(v[N - 1].z), "=r"(v[N - 1].w) : "l"(p), "n"((N - 1) * S) : "memory");
    }
    static __device__ __forceinline__ void v2(uint2* v, const void* p) {
        LdSeq<N - 1, S>::v2(v, p);
        asm volatile("ld.relaxed.gpu.global.v2.u32 {%0,%1}, [%2+%3];" : "=r"(v[N - 1].x), "=r"(v[N - 1].y) : "l"(p), "n"((N - 1) * S) : "memory");
    }
};
template <int S> struct LdSeq<0, S> {
    static __device__ __forceinline__ void v4(uint4*, const void*) {}
    static __device__ __forceinline__ void v2(uint2*, const void*) {}
};
__device__ __forceinline__ unsigned ld_rlx32(const void* p) { unsigned v; asm volatile("ld.relaxed.gpu.global.u32 %0, [%1];" : "=r"(v) : "l"(p) : "memory"); return v; }
__device__ __forceinline__ void st_rlx128(void* p, uint32_t x, uint32_t y, uint32_t z, uint32_t w) { asm volatile("st.relaxed.gpu.global.v4.u32 [%0], {%1,%2,%3,%4};" ::"l"(p), "r"(x), "r"(y), "r"(z), "r"(w) : "memory"); }
__device__ __forceinline__ void st_rlx64(void* p, uint32_t x, uint32_t y) { asm volatile("st.relaxed.gpu.global.v2.u32 [%0], {%1,%2};" ::"l"(p), "r"(x), "r"(y) : "memory"); }
__device__ __forceinline__ void stg128(void* p, uint32_t x, uint32_t y, uint32_t z, uint32_t w) { asm volatile("st.global.v4.u32 [%0], {%1,%2,%3,%4};" ::"l"(p), "r"(x), "r"(y), "r"(z), "r"(w) : "memory"); }
__device__ __forceinline__ uint32_t pack2(float lo, float hi) { uint32_t d; asm("cvt.rn.bf16x2.f32 %0, %1, %2;" : "=r"(d) : "f"(hi), "f"(lo)); return d; }
__device__ __forceinline__ uint32_t pack2relu(float lo, float hi) { uint32_t d; asm("cvt.rn.relu.bf16x2.f32 %0, %1, %2;" : "=r"(d) : "f"(hi), "f"(lo)); return d; }
__device__ __forceinline__ float blo(uint32_t v) { return __uint_as_float(v << 16); }
__device__ __forceinline__ float bhi(uint32_t v) { return __uint_as_float(v & 0xffff0000u); }
__device__ __forceinline__ float rbf(float x) { return __bfloat162float(__float2bfloat16_rn(x)); }
__device__ __forceinline__ uint32_t settag(uint32_t v, uint32_t tag) { return (v & ~1u) | tag; }
__device__ __forceinline__ uint32_t hsub2(uint32_t a, uint32_t b) { uint32_t d; asm("sub.rn.bf16x2 %0, %1, %2;" : "=r"(d) : "r"(a), "r"(b)); return d; }
__device__ __forceinline__ uint32_t hadd2(uint32_t a, uint32_t b) { uint32_t d; asm("add.rn.bf16x2 %0, %1, %2;" : "=r"(d) : "r"(a), "r"(b)); return d; }
__device__ __forceinline__ uint32_t hmul2(uint32_t a, uint32_t b) { uint32_t d; asm("mul.rn.bf16x2 %0, %1, %2;" : "=r"(d) : "r"(a), "r"(b)); return d; }
__device__ __forceinline__ uint32_t hfma2(uint32_t a, uint32_t b, uint32_t c) { uint32_t d; asm("fma.rn.bf16x2 %0, %1, %2, %3;" : "=r"(d) : "r"(a), "r"(b), "r"(c)); return d; }
__device__ __forceinline__ void mma16816(float* d, uint32_t a0, uint32_t a1, uint32_t a2, uint32_t a3, uint32_t b0, uint32_t b1) {
    asm volatile("mma.sync.aligned.m16n8k16.row.col.f32.bf16.bf16.f32 {%0,%1,%2,%3}, {%4,%5,%6,%7}, {%8,%9}, {%0,%1,%2,%3};"
                 : "+f"(d[0]), "+f"(d[1]), "+f"(d[2]), "+f"(d[3]) : "r"(a0), "r"(a1), "r"(a2), "r"(a3), "r"(b0), "r"(b1));
}
__device__ __forceinline__ void wg_fence() { asm volatile("wgmma.fence.sync.aligned;" ::: "memory"); }
__device__ __forceinline__ void wg_commit() { asm volatile("wgmma.commit_group.sync.aligned;" ::: "memory"); }
template <int N> __device__ __forceinline__ void wg_wait() { asm volatile("wgmma.wait_group.sync.aligned %0;" ::"n"(N) : "memory"); }
#define R8(a, o) "+f"(a[o]), "+f"(a[o + 1]), "+f"(a[o + 2]), "+f"(a[o + 3]), "+f"(a[o + 4]), "+f"(a[o + 5]), "+f"(a[o + 6]), "+f"(a[o + 7])
template <int TB>
__device__ __forceinline__ void wgmma176(float* d, uint32_t a0, uint32_t a1, uint32_t a2, uint32_t a3, uint64_t desc, int acc) {
    asm volatile("{\n.reg .pred p;\nsetp.ne.b32 p, %93, 0;\n"
                 "wgmma.mma_async.sync.aligned.m64n176k16.f32.bf16.bf16 {"
                 "%0,%1,%2,%3,%4,%5,%6,%7,%8,%9,%10,%11,%12,%13,%14,%15,%16,%17,%18,%19,%20,%21,%22,%23,%24,%25,%26,%27,%28,%29,%30,%31,"
                 "%32,%33,%34,%35,%36,%37,%38,%39,%40,%41,%42,%43,%44,%45,%46,%47,%48,%49,%50,%51,%52,%53,%54,%55,%56,%57,%58,%59,%60,%61,%62,%63,"
                 "%64,%65,%66,%67,%68,%69,%70,%71,%72,%73,%74,%75,%76,%77,%78,%79,%80,%81,%82,%83,%84,%85,%86,%87}, {%88,%89,%90,%91}, %92, p, 1, 1, %94;\n}\n"
                 : R8(d, 0), R8(d, 8), R8(d, 16), R8(d, 24), R8(d, 32), R8(d, 40), R8(d, 48), R8(d, 56), R8(d, 64), R8(d, 72), R8(d, 80)
                 : "r"(a0), "r"(a1), "r"(a2), "r"(a3), "l"(desc), "r"(acc), "n"(TB));
}
__device__ __forceinline__ void wgmma64(float* d, const uint32_t* a, uint64_t desc, int acc) {
    asm volatile("{\n.reg .pred p;\nsetp.ne.b32 p, %37, 0;\n"
                 "wgmma.mma_async.sync.aligned.m64n64k16.f32.bf16.bf16 {"
                 "%0,%1,%2,%3,%4,%5,%6,%7,%8,%9,%10,%11,%12,%13,%14,%15,%16,%17,%18,%19,%20,%21,%22,%23,%24,%25,%26,%27,%28,%29,%30,%31"
                 "}, {%32,%33,%34,%35}, %36, p, 1, 1, 1;\n}\n"
                 : R8(d, 0), R8(d, 8), R8(d, 16), R8(d, 24)
                 : "r"(a[0]), "r"(a[1]), "r"(a[2]), "r"(a[3]), "l"(desc), "r"(acc));
}
__device__ __forceinline__ void wgmma48ss(float* d, uint64_t da, uint64_t db, int acc) {
    asm volatile("{\n.reg .pred p;\nsetp.ne.b32 p, %26, 0;\n"
                 "wgmma.mma_async.sync.aligned.m64n48k16.f32.bf16.bf16 {"
                 "%0,%1,%2,%3,%4,%5,%6,%7,%8,%9,%10,%11,%12,%13,%14,%15,%16,%17,%18,%19,%20,%21,%22,%23"
                 "}, %24, %25, p, 1, 1, 1, 1;\n}\n"
                 : R8(d, 0), R8(d, 8), R8(d, 16)
                 : "l"(da), "l"(db), "r"(acc));
}
__device__ __forceinline__ void wgmma8ss(float* d, uint64_t da, uint64_t db, int acc) {
    asm volatile("{\n.reg .pred p;\nsetp.ne.b32 p, %6, 0;\n"
                 "wgmma.mma_async.sync.aligned.m64n8k16.f32.bf16.bf16 {%0,%1,%2,%3}, %4, %5, p, 1, 1, 1, 0;\n}\n"
                 : "+f"(d[0]), "+f"(d[1]), "+f"(d[2]), "+f"(d[3]) : "l"(da), "l"(db), "r"(acc));
}
template <int N> __device__ __forceinline__ void keep(float* a) {
#pragma unroll
    for (int i = 0; i < N; i++) asm volatile("" : "+f"(a[i])::"memory");
}
__device__ __forceinline__ void tma2d(uint32_t dst, const CUtensorMap* m, uint32_t bar, int c0, int c1) {
    asm volatile("cp.async.bulk.tensor.2d.shared::cluster.global.mbarrier::complete_tx::bytes [%0], [%1, {%3, %4}], [%2];" ::"r"(dst), "l"(m), "r"(bar), "r"(c0), "r"(c1) : "memory");
}
struct cf { float x, y; };
__device__ __forceinline__ cf cmul(cf a, cf b) { cf r; r.x = fmaf(a.x, b.x, -a.y * b.y); r.y = fmaf(a.x, b.y, a.y * b.x); return r; }
__device__ __forceinline__ cf cexp_(float re, float im) {
    float mag;
    asm("ex2.approx.ftz.f32 %0, %1;" : "=f"(mag) : "f"(re * 1.4426950408889634f));
    float k = rintf(im * 0.15915494309189535f);
    float r = fmaf(k, -6.2831854820251465f, im);
    r = fmaf(k, 1.7484556000744487e-7f, r);
    cf o; o.x = mag * __cosf(r); o.y = mag * __sinf(r);
    return o;
}
struct Params {
    const __nv_bfloat16 *x, *a_re, *a_im, *b_re, *b_im, *c_re, *c_im, *log_dt, *dskip;
    __nv_bfloat16* out;
};

__device__ __forceinline__ void issue_x(int k, uint32_t sb, int mt, const CUtensorMap* mx) {
    tma2d(sb + OFF_H + (k % 3) * 16384, mx, sb + OFF_BAR + 8 * (B_FULL + (k & 3)), 64 * ((k + (mt >> 1)) & 7), 128 * mt);
}
__device__ __forceinline__ void issue_w1(int k, uint32_t sb, int s, int mt, const CUtensorMap* mw1, const CUtensorMap* mx) {
    const uint32_t dst = sb + OFF_RING + (k & 3) * SLOT, bar = sb + OFF_BAR + 8 * (B_FULL + (k & 3));
    mbar_expect(bar, 24576 + 16384);
    if (mx && k != 3) issue_x(k, sb, mt, mx);
#pragma unroll
    for (int a = 0; a < 3; a++) tma2d(dst + a * 8192, mw1, bar, SL_ * s + 64 * a, 64 * ((k + (mt >> 1)) & 7));
}
__device__ __forceinline__ void issue_w2(int k, uint32_t sb, int s, const CUtensorMap* mw2) {
    const uint32_t dst = sb + OFF_RING + (k & 3) * SLOT, bar = sb + OFF_BAR + 8 * (B_FULL + (k & 3));
    const int pos = (k - 8) >> 1, hh = k & 1;
    const int chi = ((s >> 1) + 1 + pos) & 3;
    mbar_expect(bar, 22528);
    tma2d(dst, mw2, bar, 256 * (s & 1) + 64 * chi, SL_ * (s ^ hh));
}
__device__ __forceinline__ uint32_t rel_atom(int k, uint32_t sb) {
    uint32_t old;
    asm volatile("atom.shared.add.u32 %0, [%1], 1;" : "=r"(old) : "r"(sb + OFF_CNT + 4 * k) : "memory");
    return old;
}
__device__ __forceinline__ void refill(uint32_t old, int k, uint32_t sb, int s, int mt, const CUtensorMap* mw1, const CUtensorMap* mw2, const CUtensorMap* mx) {
    if (__builtin_expect(old == 7, 0)) {
        if (k >= 8) issue_w2(k, sb, s, mw2);
        else {
            issue_x(k, sb, mt, mx);
            if (k != 3) issue_w1(k, sb, s, mt, mw1, nullptr);
        }
    }
}
__device__ __forceinline__ void release(int k, uint32_t sb, int s, int mt, const CUtensorMap* mw1, const CUtensorMap* mw2, const CUtensorMap* mx) {
    refill(rel_atom(k, sb), k, sb, s, mt, mw1, mw2, mx);
}
__device__ __forceinline__ uint32_t kg_a(int r, int wg) { return (r & 1) ? OFF_TAB + wg * 2 * TAB_CH : OFF_STR + wg * 2 * STR_CH; }
__device__ __forceinline__ uint32_t kg_b(int r, int wg) { return OFF_STR + wg * 2 * STR_CH + ((r & 1) ? 14336 : 8192); }

__global__ void __cluster_dims__(2, 1, 1) __launch_bounds__(512, 1)
fused_kernel(const __grid_constant__ CUtensorMap mw1, const __grid_constant__ CUtensorMap mw2, const __grid_constant__ CUtensorMap mx, const Params p) {
    extern __shared__ __align__(1024) unsigned char smem[];
    const uint32_t sb = (uint32_t)__cvta_generic_to_shared(smem);
    const uint32_t bars = sb + OFF_BAR;
    const int warp = __shfl_sync(~0u, threadIdx.x >> 5, 0);
    if (warp == 0) { STAMP(0); GSTAMP(62); }
    int s, mt;
    {
        const int cl = blockIdx.x >> 1;
        int G, slot;
        if (cl < 4) { G = 0; slot = 4 + cl; }
        else if (cl < 36) { G = (cl & 7); slot = (cl - 4) >> 3; }
        else { const int j = cl - 36, q = (j * 37) >> 8, pos = j - 7 * q; G = pos < 4 ? pos + 4 : pos - 3; slot = 4 + q; }
        mt = 8 * (G >> 2) + slot;
        s = 2 * (G & 3) + (blockIdx.x & 1);
    }
    const int b = 8 * mt + s;

    const uint32_t epoch_raw = ld_rlx32(&g_epoch[b + threadIdx.y]);
    if (warp == 0) {
        const int lane = threadIdx.x;
        if (lane == 0) {
#pragma unroll
            for (int i = 0; i < 4; i++) mbar_init(bars + 8 * (B_FULL + i), 1);
            mbar_init(bars + 8 * B_LN, 1);
            asm volatile("fence.mbarrier_init.release.cluster;" ::: "memory");
            issue_w1(0, sb, s, mt, &mw1, &mx);
            mbar_expect(bars + 8 * B_LN, 16384);
            asm volatile("cp.async.bulk.shared::cluster.global.mbarrier::complete_tx::bytes [%0], [%1], %2, [%3];" ::"r"(sb + OFF_U0), "l"(p.x + (size_t)16 * b * D_), "r"(16384), "r"(bars + 8 * B_LN) : "memory");
            STAMP(48);
#pragma unroll
            for (int i = B_H; i < B_N; i++) if (i != B_LN) mbar_init(bars + 8 * i, i < B_T ? 1 : i < B_C ? 2 : i < B_S ? 1 : i < B_KF ? 4 : 8);
            asm volatile("fence.mbarrier_init.release.cluster;" ::: "memory");
        }
        sts32(sb + OFF_ONE + lane * 4, 0x3f803f80u);
        sts32(sb + OFF_CNT + lane * 4, 0);
        asm volatile("fence.proxy.async.shared::cta;" ::: "memory");
        __syncwarp();
        bar_arrive(0, 512);
        if (lane == 0) {
#pragma unroll 1
            for (int k = 1; k < 4; k++) issue_w1(k, sb, s, mt, &mw1, &mx);
            mbar_expect(bars + 8 * B_H, 22528);
            mbar_expect(bars + 8 * B_H + 8, 22528);
        }
        __syncwarp();
        STAMP(50);
    }
    if (warp >= 8) {
        asm volatile("setmaxnreg.dec.sync.aligned.u32 64;");
        const int aw = warp & 3, hh = (warp >> 2) & 1, lane = threadIdx.x & 31;
        const int ch = 16 * (b >> 2) + 2 * (b & 3) + 8 * (aw >> 1) + (aw & 1);
        int o = ch * 128 + 32 * hh + lane;
        const float ldt = ldg_bf(p.log_dt + ch);
        float n_ar = ldg_bf(p.a_re + o), n_ai = ldg_bf(p.a_im + o), n_br = ldg_bf(p.b_re + o), n_bi = ldg_bf(p.b_im + o), n_cr = ldg_bf(p.c_re + o), n_ci = ldg_bf(p.c_im + o);
        if (warp < 10) sts128(sb + OFF_U + (threadIdx.x - 256) * 16, 0, 0, 0, 0);
        bar_sync(0, 512);
        asm volatile("barrier.cluster.arrive.relaxed.aligned;" ::: "memory");
        const uint32_t tag = (__shfl_sync(~0u, epoch_raw, 0) + 1) & 1;
        if (aw == 0) STAMP(39 + hh);
        const float dt = rbf(expf(ldt));
#pragma unroll 1
        for (int it = 0; it < 2; it++) {
            const int rd = 2 * it + hh;
            const float zr = dt * n_ar, zi = dt * n_ai;
            const cf dB = {dt * n_br, dt * n_bi}, C = {n_cr, n_ci};
            o += 64;
            if (it == 0) { n_ar = ldg_bf(p.a_re + o); n_ai = ldg_bf(p.a_im + o); n_br = ldg_bf(p.b_re + o); n_bi = ldg_bf(p.b_im + o); n_cr = ldg_bf(p.c_re + o); n_ci = ldg_bf(p.c_im + o); }
            cf g0 = cmul(C, dB); g0.y = -g0.y;
            const cf w1 = cexp_(zr, -zi), H1 = cexp_(256.f * zr, -256.f * zi), w8 = cexp_(8.f * zr, 8.f * zi);
            const uint32_t fa = sb + kg_a(rd, aw >> 1) + (aw & 1) * 4096 + lane * 16, fb = sb + kg_b(rd, aw >> 1) + (aw & 1) * 3072 + lane * 16;
            if (it) mbar_wait(bars + 8 * (B_KF + hh), 0);
            {
                cf E[4], O[4];
                E[0].x = 1.f; E[0].y = 0.f; E[1] = w8; E[2] = cmul(w8, w8); E[3] = cmul(E[2], w8);
                const cf F4 = cmul(E[2], E[2]);
#pragma unroll
                for (int q = 0; q < 4; q++) {
#pragma unroll
                    for (int i = 0; i < 4; i++) O[i] = (q == 0 && i == 0) ? F4 : cmul(E[i], F4);
                    sts128(fa + (2 * q) * 512, pack2(E[0].x, E[1].x), pack2(E[2].x, E[3].x), pack2(O[0].x, O[1].x), pack2(O[2].x, O[3].x));
                    sts128(fa + (2 * q + 1) * 512, pack2(E[0].y, E[1].y), pack2(E[2].y, E[3].y), pack2(O[0].y, O[1].y), pack2(O[2].y, O[3].y));
                    if (q < 3) {
#pragma unroll
                        for (int i = 0; i < 4; i++) E[i] = cmul(O[i], F4);
                    }
                }
            }
            {
                cf gg[8];
                gg[0] = g0;
#pragma unroll
                for (int i = 1; i < 8; i++) gg[i] = cmul(gg[i - 1], w1);
                sts128(fb, pack2(gg[0].x, gg[1].x), pack2(gg[2].x, gg[3].x), pack2(gg[4].x, gg[5].x), pack2(gg[6].x, gg[7].x));
                sts128(fb + 512, pack2(gg[0].y, gg[1].y), pack2(gg[2].y, gg[3].y), pack2(gg[4].y, gg[5].y), pack2(gg[6].y, gg[7].y));
                const cf H2 = cmul(H1, H1);
                const cf G8 = cmul(gg[0], H1), G9 = cmul(gg[2], H1), G10 = cmul(gg[4], H1), G11 = cmul(gg[6], H1);
                const cf G12 = cmul(gg[0], H2), G13 = cmul(gg[4], H2), G14 = cmul(G12, H1), G15 = cmul(G13, H1);
                sts128(fb + 1024, pack2(G8.x, G9.x), pack2(G10.x, G11.x), pack2(G12.x, G13.x), pack2(G14.x, G15.x));
                sts128(fb + 1536, pack2(G8.y, G9.y), pack2(G10.y, G11.y), pack2(G12.y, G13.y), pack2(G14.y, G15.y));
                const cf G16 = cmul(G12, H2), G17 = cmul(G16, H1), G18 = cmul(G16, H2), G19 = cmul(G17, H2), G20 = cmul(G18, H2);
                sts128(fb + 2048, pack2(G16.x, G17.x), pack2(G18.x, G19.x), pack2(G20.x, 0.f), 0);
                sts128(fb + 2560, pack2(G16.y, G17.y), pack2(G18.y, G19.y), pack2(G20.y, 0.f), 0);
            }
            asm volatile("fence.proxy.async.shared::cta;" ::: "memory");
            __syncwarp();
            if (lane == 0) mbar_arrive(bars + 8 * (B_KG + rd));
            if (aw == 0) STAMP(41 + rd);
            if (it == 0) {
                mbar_wait(bars + 8 * B_LN, 0);
                if (warp == 8) STAMP(52);
                const int row = 2 * (warp - 8) + (lane >> 4);
                const uint32_t rb = sb + OFF_U0 + row * 1024, ra = rb + (lane & 15) * 16;
                uint4 v[4];
                const float x0 = blo(lds32(rb));
#pragma unroll
                for (int i = 0; i < 4; i++) v[i] = lds128(ra + i * 256);
                uint32_t* w = &v[0].x;
                float s0 = 0.f, s1 = 0.f, q0 = 0.f, q1 = 0.f;
#pragma unroll
                for (int j = 0; j < 16; j++) {
                    const float d0 = blo(w[j]) - x0, d1 = bhi(w[j]) - x0;
                    s0 += d0; s1 += d1; q0 = fmaf(d0, d0, q0); q1 = fmaf(d1, d1, q1);
                }
                s0 += s1; q0 += q1;
#pragma unroll
                for (int of = 1; of < 16; of <<= 1) { s0 += __shfl_xor_sync(~0u, s0, of); q0 += __shfl_xor_sync(~0u, q0, of); }
                if (warp == 8) STAMP(53);
                s0 *= 1.f / 512.f;
                const uint32_t mb = __float_as_uint(rbf(x0 + s0));
                const float sd = rbf(sqrtf(rbf(rbf(fmaxf(fmaf(q0, 1.f / 512.f, -s0 * s0), 0.f)) + 1e-5f)));
                const float r = 1.0f / sd, rh = rbf(r);
                const uint32_t mm = mb | (mb >> 16), rh2 = pack2(rh, rh), rl2 = pack2(r - rh, r - rh);
                if ((lane & 15) == 0) st_rlx64(&g_stats[16 * b + row], mb | tag, __float_as_uint(sd));
#pragma unroll
                for (int j = 0; j < 16; j++) { const uint32_t d = hsub2(w[j], mm); w[j] = hfma2(d, rh2, hmul2(d, rl2)); }
#pragma unroll
                for (int i = 0; i < 4; i++) sts128((ra ^ ((lane & 16) << 2)) + i * 256, v[i].x, v[i].y, v[i].z, v[i].w);
                if (warp == 8) STAMP(57);
                bar_sync(1, 256);
                if (warp == 8) STAMP(58);
                const uint32_t ta = sb + OFF_U0 + (2 * (lane >> 3) + (lane & 1)) * 1024 + aw * 256 + hh * 128 + ((((lane & 7) >> 1) ^ ((lane & 1) << 2)) << 4);
                uint4* up = &g_u[((32 * aw + 16 * hh + 4 * ((lane >> 1) & 1) + (lane >> 3)) * 128 + b) * 8];
                const int c0 = ((((lane >> 2) & 1) << 1) | (lane & 1)) ^ (b & 7);
#pragma unroll
                for (int i = 0; i < 4; i++) ldsm4t(w + 4 * i, (ta ^ ((i & 2) << 5)) + (i & 1) * 8192);
#pragma unroll
                for (int i = 0; i < 4; i++) st_rlx128(up + (i >> 1) * 8192 + (c0 ^ ((i & 1) << 2)), settag(v[i].x, tag), v[i].y, v[i].z, v[i].w);
                if (hh) bar_arrive(8, 256);
                if (warp == 8) STAMP(56);
            }
        }
      if (hh) {
            const int t3 = threadIdx.x - 384;
            if (aw == 3) {
                uint4 v, u;
                int it = 0;
                for (;;) {
                    v = ld_rlx128((const uint4*)&g_stats[128 * mt] + lane); u = ld_rlx128((const uint4*)&g_stats[128 * mt] + 32 + lane);
                    if (!(((v.x ^ tag) | (v.z ^ tag) | (u.x ^ tag) | (u.z ^ tag)) & 1)) break;
                    if (++it > (1 << 20)) GFAIL(__LINE__);
                }
                sts128(sb + OFF_STAT + lane * 16, v.x & ~1u, v.y, v.z & ~1u, v.w);
                sts128(sb + OFF_STAT + 512 + lane * 16, u.x & ~1u, u.y, u.z & ~1u, u.w);
            }
            if (t3 < 88) {
                float a0 = 0.f, a1 = 0.f;
                {
                    uint2 v[16];
                    int it = 0;
                    for (;;) {
                        uint32_t bad = 0;
                        LdSeq<16, 768>::v2(v, &g_cs[s * 16 * 96 + t3]);
#pragma unroll
                        for (int i = 0; i < 16; i++) bad |= v[i].x ^ tag;
                        if (!(bad & 1)) break;
                        if (++it > (1 << 20)) GFAIL(__LINE__);
                    }
#pragma unroll
                    for (int i = 0; i < 16; i++) { a0 += __uint_as_float(v[i].x & ~1u); a1 += __uint_as_float(v[i].y); }
                }
                const uint32_t ca = sb + OFF_CS + (16 * (t3 >> 3) + (t3 & 7)) * 16;
                sts128(ca, pack2(a0, a0 - rbf(a0)), 0, 0, 0);
                sts128(ca + 128, pack2(a1, a1 - rbf(a1)), 0, 0, 0);
                asm volatile("fence.proxy.async.shared::cta;" ::: "memory");
            }
            __syncwarp();
            if (lane == 0) mbar_arrive(bars + 8 * B_S);
            if (aw == 1) STAMP(31);
            {
            const uint32_t stg = sb + OFF_STR + aw * STR_CH, tab = sb + OFF_TAB + aw * TAB_CH + lane * 4;
            auto Kt = [&](int l) { return __uint_as_float(lds32(stg + (l + (l >> 5)) * 4)); };
            const int pl = (lane + 31) & 31;
            mbar_wait(bars + 8 * (B_KT + (aw >> 1)), 0);
            const float k1024 = Kt(1024);
            sts32(tab + TAB_FIX, pack2((lane == 19 || lane == 20) ? k1024 : 0.f, (lane == 20 || lane == 21) ? k1024 : 0.f));
            sts32(tab + TAB_FIX + 128, 0);
            {
                float v[8];
#pragma unroll
                for (int i = 0; i < 8; i++) {
                    const int ss = i >> 1, x = 16 + 32 * (i & 1) + lane, off = 8 + 8 * (ss & 1) + 4 * (ss >> 1), hi = ss == 3 ? 63 : 64;
                    v[i] = (x >= 32 && x < hi) ? Kt(16 * x + off) : 0.f;
                }
#pragma unroll
                for (int i = 0; i < 8; i++) {
                    const float pv = __shfl_sync(~0u, lane == 31 ? ((i & 1) ? v[i - 1] : 0.f) : v[i], pl);
                    sts32(tab + TAB_Q2 + i * 128, pack2(v[i], pv));
                }
            }
            {
                float v[5];
#pragma unroll
                for (int i = 0; i < 5; i++) {
                    const int y = 32 * i + lane, ss = y >= 80, x = 48 + y - 80 * ss, off = ss ? 8 : 16;
                    v[i] = x >= 64 ? Kt(16 * x + off) : 0.f;
                }
#pragma unroll
                for (int i = 0; i < 5; i++) {
                    float pv = __shfl_sync(~0u, lane == 31 ? (i ? v[i - 1] : 0.f) : v[i], pl);
                    if (i == 2 && lane == 16) pv = 0.f;
                    sts32(tab + TAB_Q3 + i * 128, pack2(v[i], pv));
                }
            }
            }
            __syncwarp();
            if (lane == 0) mbar_arrive(bars + 8 * (B_T + aw));
      } else {
        const float dsk = ldg_bf(p.dskip + ch);
        bar_sync(8, 256);
        {
            const int t3 = threadIdx.x - 256;
            const uint4* src = &g_u[b * 1024 + t3];
            uint4 v[8];
            int it = 0;
            for (;;) {
                uint32_t bad = 0;
                LdSeq<8, 2048>::v4(v, src);
#pragma unroll
                for (int i = 0; i < 8; i++) bad |= v[i].x ^ tag;
                if (!(bad & 1)) break;
                if (++it > (1 << 20)) GFAIL(__LINE__);
            }
#pragma unroll
            for (int i = 0; i < 8; i++) sts128(sb + OFF_U0 + (128 * i + t3) * 16, v[i].x & ~1u, v[i].y, v[i].z, v[i].w);
            __syncwarp();
            if (lane == 0) mbar_arrive(bars + 8 * B_U);
            if (aw == 1) STAMP(61);
        }
        const uint32_t stg = sb + OFF_STR + aw * STR_CH;
        mbar_wait(bars + 8 * (B_KT + (aw >> 1)), 0);
        if (aw == 0) STAMP(45);
        {
            const uint32_t tab = sb + OFF_TAB + aw * TAB_CH + lane * 4;
            auto Kt = [&](int l) { return __uint_as_float(lds32(stg + (l + (l >> 5)) * 4)); };
            const int pl = (lane + 31) & 31;
            float last = 0.f;
#pragma unroll
            for (int hf = 0; hf < 2; hf++) {
                float v[9];
#pragma unroll
                for (int k = 0; k < 9; k++) {
                    const int i = 9 * hf + k, x = 32 * i + lane - 16;
                    int l = x;
                    if (i >= 8) { const int r = (x + 1) & ~3; l = (((x & 1) && x > 256) || x >= 512) ? r : x; }
                    if (i == 17) v[k] = 0.f;
                    else if (i == 0) { v[k] = x >= 0 ? Kt(l) : 0.f; if (x == 0) v[k] += dsk; }
                    else if (i == 16) v[k] = x <= 517 ? Kt(l) : 0.f;
                    else v[k] = Kt(l);
                }
#pragma unroll
                for (int k = 0; k < 9; k++) {
                    const float pv = __shfl_sync(~0u, lane == 31 ? last : v[k], pl);
                    last = v[k];
                    sts32(tab + (9 * hf + k) * 128, pack2(v[k], pv));
                }
            }
        }
        __syncwarp();
        if (lane == 0) mbar_arrive(bars + 8 * (B_T + aw));
        if (aw == 0) STAMP(32);
        mbar_wait(bars + 8 * (B_T + aw), 0);
        mbar_wait(bars + 8 * B_U, 0);
        if (aw == 0) STAMP(33);
        if (lane < 4) sts128(stg + lane * 16, 0, 0, 0, 0);
        const int cu = ((aw & 1) << 1) | (aw >> 1);
#pragma unroll 1
        for (int t = 0; t < 3; t++) {
            const int j = 32 * t + lane;
            const uint32_t ub = sb + OFF_U0 + j * 128;
            float P[36];
            {
                uint4 v[5];
                v[0] = lds128(ub - 256 + (((cu + 4) ^ ((j - 2) & 7)) << 4));
                v[1] = lds128(ub - 128 + ((cu ^ ((j - 1) & 7)) << 4));
                v[2] = lds128(ub - 128 + (((cu + 4) ^ ((j - 1) & 7)) << 4));
                v[3] = lds128(ub + ((cu ^ (j & 7)) << 4));
                v[4] = lds128(ub + (((cu + 4) ^ (j & 7)) << 4));
                const uint32_t* w = &v[0].x;
                P[4] = 0.f;
#pragma unroll
                for (int i = 4; i < 35; i++) P[i + 1] = P[i] + ((i & 1) ? bhi(w[i >> 1]) : blo(w[i >> 1]));
            }
            const uint32_t o1 = stg + 64 + j * 64, o2 = stg + 6208 + j * 64;
            const int sw = (j >> 1) & 3;
#pragma unroll
            for (int h = 0; h < 2; h++) {
                const int q = 8 * h;
                sts128(o1 + ((h ^ sw) << 4), pack2(P[q + 19] - P[q + 14], P[q + 20] - P[q + 15]), pack2(P[q + 21] - P[q + 16], P[q + 22] - P[q + 17]),
                       pack2(P[q + 23] - P[q + 18], P[q + 24] - P[q + 19]), pack2(P[q + 25] - P[q + 20], P[q + 26] - P[q + 21]));
                sts128(o1 + (((2 + h) ^ sw) << 4), pack2(P[q + 14] - P[q + 11], P[q + 15] - P[q + 12]), pack2(P[q + 16] - P[q + 13], P[q + 17] - P[q + 14]),
                       pack2(P[q + 18] - P[q + 15], P[q + 19] - P[q + 16]), pack2(P[q + 20] - P[q + 17], P[q + 21] - P[q + 18]));
                if (t < 2) {
                    sts128(o2 + ((h ^ sw) << 4), pack2(P[q + 13] - P[q + 4], P[q + 14] - P[q + 5]), pack2(P[q + 15] - P[q + 6], P[q + 16] - P[q + 7]),
                           pack2(P[q + 17] - P[q + 8], P[q + 18] - P[q + 9]), pack2(P[q + 19] - P[q + 10], P[q + 20] - P[q + 11]));
                    sts128(o2 + (((2 + h) ^ sw) << 4), pack2(P[q + 20] - P[q + 13], P[q + 21] - P[q + 14]), pack2(P[q + 22] - P[q + 15], P[q + 23] - P[q + 16]),
                           pack2(P[q + 24] - P[q + 17], P[q + 25] - P[q + 18]), pack2(P[q + 26] - P[q + 19], P[q + 27] - P[q + 20]));
                }
            }
        }
        __syncwarp();
        if (lane == 0) mbar_arrive(bars + 8 * (B_C + aw));
        if (aw == 0) STAMP(36);
        mbar_wait(bars + 8 * B_Y, 0);
        if (aw == 0) STAMP(37);
        {
            const int at = threadIdx.x - 256;
            const uint32_t ya = sb + OFF_STR + ((at ^ (((at >> 4) & 1) << 2)) << 3);
            uint4* dst = &g_ao[(b * 128 + 2 * (at >> 3)) * 8 + (at & 7)];
#pragma unroll 2
            for (int it = 0; it < 4; it++) {
                uint32_t o[2][4];
#pragma unroll
                for (int k = 0; k < 4; k++) {
                    const uint2 v0 = lds64(ya + k * STR_CH + it * 1024), v1 = lds64(ya + k * STR_CH + 4096 + it * 1024);
                    o[0][k] = hadd2(v0.x, v1.x); o[1][k] = hadd2(v0.y, v1.y);
                }
                st_rlx128(dst + it * 256, settag(o[0][0], tag), o[0][1], o[0][2], o[0][3]);
                st_rlx128(dst + it * 256 + 8, settag(o[1][0], tag), o[1][1], o[1][2], o[1][3]);
            }
        }
        if (aw == 0) STAMP(38);
      }
        __syncwarp();
        asm volatile("barrier.cluster.wait.aligned;" ::: "memory");
    } else {
        asm volatile("setmaxnreg.inc.sync.aligned.u32 192;");
        const int wg = warp >> 2, w = warp & 3, tid = threadIdx.x, lane = tid & 31, g = lane >> 2, c = lane & 3;
        const int rloc = 64 * wg + 16 * w + g;
        const uint64_t dlo = ((sb + OFF_RING) & 0x3ffffu) >> 4;
        const uint64_t d2 = ((uint64_t)1 << 62) | ((uint64_t)(1024 >> 4) << 32) | ((uint64_t)(8192 >> 4) << 16) | dlo;
        uint32_t hown[44], hpeer[44];
        const uint32_t epoch = __shfl_sync(~0u, epoch_raw, 0) + 1, tag = epoch & 1;
        if (warp == 0) STAMP(13);
        {
            const uint32_t xa = sb + OFF_H + (16 * warp + (lane & 15)) * 128 + (((lane >> 4) ^ (lane & 7)) << 4);
            uint32_t xr[2][16];
            if (warp) bar_sync(0, 512);
            if (warp == 1) STAMP(14);
            const uint64_t dk = ((uint64_t)(1024 >> 4) << 32) | ((uint64_t)(512 >> 4) << 16) | dlo;
            float acc[88], kacc[24], cs[12];
            uint32_t xs = xa, old = 0;
#pragma unroll 1
            for (int it = 0; it < 4; it++) {
#pragma unroll
                for (int j = 0; j < 2; j++) {
                    const int st = 2 * it + j, kr = j ? 3 * (it >> 1) : it - 1;
                    const bool kg = it & (j ? 1 : 2);
                    mbar_wait(bars + 8 * (B_FULL + (st & 3)), it >> 1);
#pragma unroll
                    for (int kk = 0; kk < 4; kk++) ldsm4(&xr[j][4 * kk], xs ^ (kk << 5));
                    xs += xs < xa + 32768 ? 16384 : -32768;
                    refill(old, st + 2, sb, s, mt, &mw1, &mw2, &mx);
                    if (kg) mbar_wait(bars + 8 * (B_KG + kr), 0);
                    if (warp == 0) STAMP(1 + st);
                    const uint64_t desc = d2 + (st & 3) * (SLOT >> 4);
                    wg_fence();
                    if (kg) {
                        const uint64_t da = dk + (kg_a(kr, wg) >> 4), db = dk + (kg_b(kr, wg) >> 4);
#pragma unroll
                        for (int kk = 0; kk < 4; kk++) wgmma48ss(kacc, da + kk * 8, db + kk * 8, kr > 0 || kk > 0);
                    } else if (j == 0 && it == 0) {
                        const uint64_t da = d2 + (mt & 1) * (4096 >> 4), db = dlo + (OFF_ONE >> 4);
#pragma unroll
                        for (int a = 0; a < 3; a++) { wgmma8ss(cs + 4 * a, da + a * 512, db, 0); wgmma8ss(cs + 4 * a, da + a * 512 + 128, db, 1); }
                    }
                    wg_commit();
#pragma unroll
                    for (int kk = 0; kk < 4; kk++) {
                        const uint32_t* R = &xr[j][4 * kk];
                        wgmma176<1>(acc, R[0], R[1], R[2], R[3], desc + kk * 128, (st | kk) != 0);
                    }
                    wg_commit();
                    wg_wait<1>();
                    if (lane == 0) {
                        if (it == 2 - j) mbar_arrive(bars + 8 * (B_KF + 1 - j));
                        old = rel_atom(st + 3, sb);
                    }
                    if (j == 1 && it == 0) {
                        keep<12>(cs);
                        const int t = 32 * c + w * 8 + g;
                        const float v0 = c == 0 ? cs[0] : c == 1 ? cs[4] : cs[8], v1 = c == 0 ? cs[2] : c == 1 ? cs[6] : cs[10];
                        if (wg && t < 88) st_rlx64(&g_cs[(s * 16 + mt) * 96 + t], settag(__float_as_uint(v0), tag), __float_as_uint(v1));
                    }
                }
            }
            refill(old, 10, sb, s, mt, &mw1, &mw2, &mx);
            __syncwarp();
            asm volatile("barrier.cluster.arrive.relaxed.aligned;" ::: "memory");
            {
                keep<24>(kacc);
                bar_sync(6 + wg, 128);
                const uint32_t kt = sb + OFF_STR + (2 * wg + (w >> 1)) * STR_CH;
                const int jo = 8 * (16 * (w & 1) + g);
#pragma unroll
                for (int n = 0; n < 3; n++)
#pragma unroll
                    for (int e = 0; e < 2; e++) {
                        const int nn = 2 * c + e;
                        const int l1 = n == 0 ? nn : n == 1 ? (nn < 4 ? 256 + 2 * nn : 512 + 256 * ((nn - 4) >> 1) + 4 * (nn & 1)) : (nn < 4 ? 1024 + 256 * nn : 2044 + nn);
#pragma unroll
                        for (int h = 0; h < 2; h++) {
                            const int l = l1 + jo + 64 * h, i = 4 * n + 2 * h + e;
                            sts32(kt + (l + (l >> 5)) * 4, __float_as_uint((w & 2) ? kacc[12 + i] : kacc[i]));
                        }
                    }
                __syncwarp();
                if (lane == 0) mbar_arrive(bars + 8 * (B_KT + wg));
            }
            mbar_wait(bars + 8 * B_S, 0);
            {
                const uint32_t m0 = lds32(sb + OFF_STAT + rloc * 8) ^ 0x80000000u, m1 = lds32(sb + OFF_STAT + (rloc + 8) * 8) ^ 0x80000000u;
                const uint32_t a0 = c == 0 ? m0 | (m0 >> 16) : 0u, a1 = c == 0 ? m1 | (m1 >> 16) : 0u;
                wg_fence();
                wgmma176<0>(acc, a0, a1, 0u, 0u, ((uint64_t)(128 >> 4) << 32) | (dlo + (OFF_CS >> 4)), 1);
                wg_commit();
            }
            wg_wait<0>();
            keep<88>(acc);
            if (lane == 0) release(11, sb, s, mt, &mw1, &mw2, &mx);
            if (w == 0) STAMP(9 + wg);
#pragma unroll
            for (int j = 0; j < 44; j++) hown[j] = pack2relu(acc[2 * j], acc[2 * j + 1]);
            asm volatile("barrier.cluster.wait.acquire.aligned;" ::: "memory");
            uint32_t rdst, rbar;
            asm("mapa.shared::cluster.u32 %0, %1, %2;" : "=r"(rdst) : "r"(sb + OFF_H + tid * 16), "r"((s & 1) ^ 1));
            asm("mapa.shared::cluster.u32 %0, %1, %2;" : "=r"(rbar) : "r"(bars + 8 * (B_H + wg)), "r"((s & 1) ^ 1));
#pragma unroll
            for (int k = 0; k < 11; k++)
                asm volatile("st.async.weak.shared::cluster.mbarrier::complete_tx::bytes.v4.b32 [%0], {%1,%2,%3,%4}, [%5];" ::"r"(rdst + k * 4096),
                             "r"(hown[4 * k]), "r"(hown[4 * k + 1]), "r"(hown[4 * k + 2]), "r"(hown[4 * k + 3]), "r"(rbar) : "memory");
        }
        if (w == 0) STAMP(11 + wg);
        {
            const int chl = 2 * wg + (w >> 1), par = w & 1;
            const uint32_t tab = sb + OFF_TAB + chl * TAB_CH, str = sb + OFF_STR + chl * STR_CH;
            const int mi = lane >> 3, r7 = lane & 7;
            float y[16][4];
#pragma unroll
            for (int i = 0; i < 64; i++) (&y[0][0])[i] = 0.f;
            mbar_wait(bars + 8 * (B_T + chl), 0);
            mbar_wait(bars + 8 * B_U, 0);
            if (w == 0) STAMP(15 + wg);
            const uint32_t ta = tab + (16 + g - 2 * c + 16 * par) * 4;
            const int cu = (((chl & 1) << 1) | wg) + 4 * (mi & 1);
            {
                uint32_t A[6][3];
#pragma unroll
                for (int om = 0; om < 6; om++) {
                    const uint32_t a = ta + (om < 5 ? 512 * om : TAB_FIX);
                    A[om][0] = lds32(a); A[om][1] = lds32(a + 32); A[om][2] = lds32(a - 32);
                }
                const uint32_t ua = sb + OFF_U0 + (8 * (mi >> 1) + r7 - par) * 128 + ((cu ^ ((r7 - par) & 7)) << 4);
#pragma unroll
                for (int mp = 0; mp < 8; mp++) {
                    uint32_t B[4];
                    ldsm4(B, ua + mp * 2048);
#pragma unroll
                    for (int om = 0; om < 6; om++)
#pragma unroll
                        for (int t = 0; t < 2; t++) {
                            const int o = 2 * mp + t + (om < 5 ? om : 8);
                            if (o < 16) mma16816(y[o], A[om][0], A[om][1], A[om][2], A[om][0], B[2 * t], B[2 * t + 1]);
                        }
                }
            }
#pragma unroll 1
            for (int dl = 2; dl < 8; dl += 2) {
                uint32_t A[4][3];
#pragma unroll
                for (int om = 0; om < 4; om++) {
                    const uint32_t a = ta + 512 * om + 64 * dl;
                    A[om][0] = lds32(a); A[om][1] = lds32(a + 32); A[om][2] = lds32(a - 32);
                }
                const uint32_t ua = sb + OFF_U0 + (8 * (mi >> 1) + r7 - par - dl) * 128 + ((cu ^ ((r7 - par - dl) & 7)) << 4);
#pragma unroll
                for (int mp = 0; mp < 8; mp++) {
                    uint32_t B[4];
                    ldsm4(B, ua + mp * 2048);
#pragma unroll
                    for (int om = 0; om < 4; om++)
#pragma unroll
                        for (int t = 0; t < 2; t++) {
                            const int o = 2 * mp + t + om;
                            if (o < 16) mma16816(y[o], A[om][0], A[om][1], A[om][2], A[om][0], B[2 * t], B[2 * t + 1]);
                        }
                }
            }
            if (w == 0) STAMP(17 + wg);
            mbar_wait(bars + 8 * (B_C + chl), 0);
            const int hq = mi & 1;
#pragma unroll 1
            for (int s2 = 0; s2 < 2; s2++) {
                uint32_t Q[7];
                const uint32_t qa = tab + TAB_Q2 + (par + 2 * s2) * 256 + (8 + g - 2 * c) * 4;
#pragma unroll
                for (int i = 0; i < 7; i++) Q[i] = lds32(qa + 32 * i);
                const int blk = 8 * (mi >> 1) + r7 - (par & (hq ^ 1));
                const uint32_t za = str + 64 + blk * 64 + (((2 * s2 + (hq ^ par)) ^ ((blk >> 1) & 3)) << 4);
#pragma unroll
                for (int k = 0; k < 6; k++) {
                    uint32_t A[4];
                    ldsm4t(A, za + k * 1024);
#pragma unroll
                    for (int d = 4; d < 10; d++)
                        if (2 * k + d < 16) mma16816(y[2 * k + d], A[0], A[1], A[2], A[3], Q[d - 3], Q[d - 4]);
                }
            }
            {
                uint32_t Q[9];
                const uint32_t qa = tab + TAB_Q3 + par * 320 + (8 + g - 2 * c) * 4;
#pragma unroll
                for (int i = 0; i < 9; i++) Q[i] = lds32(qa + 32 * i);
                const int blk = 8 * (mi >> 1) + r7;
                const uint32_t za = str + 6208 + blk * 64 + (((2 * par + hq) ^ ((blk >> 1) & 3)) << 4);
#pragma unroll
                for (int k = 0; k < 4; k++) {
                    uint32_t A[4];
                    ldsm4t(A, za + k * 1024);
#pragma unroll
                    for (int d = 8; d < 16; d++)
                        if (2 * k + d < 16) mma16816(y[2 * k + d], A[0], A[1], A[2], A[3], Q[d - 7], Q[d - 8]);
                }
            }
            if (w == 0) STAMP(19 + wg);
            bar_sync(2 + chl, 64);
            const uint32_t yo = str + par * 4096 + (((c * 8 + g) ^ ((c >> 1) << 2)) << 3);
#pragma unroll
            for (int t = 0; t < 16; t++) sts64(yo + t * 256, pack2(y[t][0], y[t][2]), pack2(y[t][1], y[t][3]));
            __syncwarp();
            if (lane == 0) mbar_arrive(bars + 8 * B_Y);
        }
        {
            float acc[2][32];
            const int P = s >> 1, hf = s & 1;
            const uint4* pin = &g_part[(b * 3 * 2 + wg) * 512 + (tid & 127)];
#pragma unroll
            for (int pos = 0; pos < 4; pos++) {
                float* ac = acc[pos & 1];
                float* ap = acc[(pos & 1) ^ 1];
                const int k0 = 8 + 2 * pos;
                mbar_wait(bars + 8 * (B_FULL + (k0 & 3)), (k0 >> 2) & 1);
                if (warp == 0) STAMP(21 + 2 * pos);
                {
                    const uint64_t desc = d2 + (k0 & 3) * (SLOT >> 4);
                    wg_fence();
#pragma unroll
                    for (int k = 0; k < 11; k++) wgmma64(ac, &hown[4 * k], desc + k * 128, k != 0);
                    wg_commit();
                }
                if (pos == 0) {
                    mbar_wait_cluster(bars + 8 * (B_H + wg), 0);
#pragma unroll
                    for (int k = 0; k < 11; k++) {
                        uint4 v = lds128(sb + OFF_H + (k * 256 + tid) * 16);
                        hpeer[4 * k] = v.x; hpeer[4 * k + 1] = v.y; hpeer[4 * k + 2] = v.z; hpeer[4 * k + 3] = v.w;
                    }
                } else {
                    wg_wait<1>();
                    keep<32>(ap);
                    if (pos < 3 && lane == 0) release(k0 + 3, sb, s, mt, &mw1, &mw2, &mx);
                    const int dest = (b & ~7) + 2 * ((P + pos) & 3) + hf;
                    uint4* po = &g_part[((dest * 3 + pos - 1) * 2 + wg) * 512 + (tid & 127)];
#pragma unroll
                    for (int i = 0; i < 4; i++)
                        st_rlx128(po + i * 128, settag(pack2(ap[8 * i], ap[8 * i + 1]), tag), pack2(ap[8 * i + 2], ap[8 * i + 3]), pack2(ap[8 * i + 4], ap[8 * i + 5]), pack2(ap[8 * i + 6], ap[8 * i + 7]));
                }
                mbar_wait(bars + 8 * (B_FULL + ((k0 + 1) & 3)), ((k0 + 1) >> 2) & 1);
                if (warp == 0) STAMP(22 + 2 * pos);
                {
                    const uint64_t desc = d2 + ((k0 + 1) & 3) * (SLOT >> 4);
                    wg_fence();
#pragma unroll
                    for (int k = 0; k < 11; k++) wgmma64(ac, &hpeer[4 * k], desc + k * 128, 1);
                    wg_commit();
                }
                if (pos < 2) {
                    wg_wait<1>();
                    if (lane == 0) release(k0 + 4, sb, s, mt, &mw1, &mw2, &mx);
                }
            }
            float* ac = acc[1];
            float* tt = acc[0];
            const float sd0 = __uint_as_float(lds32(sb + OFF_STAT + rloc * 8 + 4)), sd1 = __uint_as_float(lds32(sb + OFF_STAT + (rloc + 8) * 8 + 4));
            uint32_t u[16], v[16];
            poll8<2048, 65536>(u, v, pin, &g_ao[((4 * (16 * hf + 4 * P) + c) * 128 + 8 * mt + warp) * 8 + g], tag);
            if (warp == 0) STAMP(29);
#pragma unroll
            for (int i = 0; i < 4; i++) {
                u[4 * i] &= ~1u; v[4 * i] &= ~1u;
#pragma unroll
                for (int t = 0; t < 2; t++) {
                    float* q = tt + 8 * i + 4 * t;
                    q[0] = fmaf(blo(v[4 * i + 2 * t]), sd0, blo(u[4 * i + 2 * t]));
                    q[1] = fmaf(blo(v[4 * i + 2 * t + 1]), sd0, bhi(u[4 * i + 2 * t]));
                    q[2] = fmaf(bhi(v[4 * i + 2 * t]), sd1, blo(u[4 * i + 2 * t + 1]));
                    q[3] = fmaf(bhi(v[4 * i + 2 * t + 1]), sd1, bhi(u[4 * i + 2 * t + 1]));
                }
            }
            wg_wait<1>();
            uint4 xres[4];
            {
                const __nv_bfloat16* xq = p.x + (size_t)(128 * mt + 16 * warp + (lane >> 3)) * D_ + 256 * hf + 64 * P + 8 * (lane & 7);
#pragma unroll
                for (int i = 0; i < 4; i++) xres[i] = ldg_nc128(xq + 4 * i * D_);
            }
            const float r0 = 1.0f / sd0, r1 = 1.0f / sd1;
            poll8<2048, 2048>(u, v, pin + 1024, pin + 2048, tag);
            if (warp == 0) STAMP(30);
            wg_wait<0>();
            keep<32>(ac);
            if (warp == 0) STAMP(46);
            const uint32_t os = sb + OFF_H + warp * 2048;
            const int mi = lane >> 3, r7 = lane & 7;
#pragma unroll
            for (int jj = 0; jj < 4; jj++) {
                uint32_t o[4];
                u[4 * jj] &= ~1u; v[4 * jj] &= ~1u;
#pragma unroll
                for (int t = 0; t < 4; t++) {
                    const float r = (t & 1) ? r1 : r0;
                    o[t] = pack2(((ac[8 * jj + 2 * t] + tt[8 * jj + 2 * t]) + (blo(u[4 * jj + t]) + blo(v[4 * jj + t]))) * r,
                                 ((ac[8 * jj + 2 * t + 1] + tt[8 * jj + 2 * t + 1]) + (bhi(u[4 * jj + t]) + bhi(v[4 * jj + t]))) * r);
                }
                stsm4(os + (8 * (mi & 1) + r7) * 128 + (((2 * jj + (mi >> 1)) ^ r7) << 4), o[0], o[1], o[2], o[3]);
            }
            __syncwarp();
            __nv_bfloat16* oq = p.out + (size_t)(128 * mt + 16 * warp + (lane >> 3)) * D_ + 256 * hf + 64 * P + 8 * (lane & 7);
#pragma unroll
            for (int i = 0; i < 4; i++) {
                const int row = 4 * i + (lane >> 3);
                uint4 q = lds128(os + row * 128 + (((lane & 7) ^ (row & 7)) << 4));
                stg128(oq + 4 * i * D_, hadd2(q.x, xres[i].x), hadd2(q.y, xres[i].y), hadd2(q.z, xres[i].z), hadd2(q.w, xres[i].w));
            }
            if (tid == 0) g_epoch[b] = epoch;
            if (warp == 0) { STAMP(47); GSTAMP(63); }
        }
    }
}

typedef CUresult (*EncodeFn)(CUtensorMap*, CUtensorMapDataType, cuuint32_t, void*, const cuuint64_t*, const cuuint64_t*, const cuuint32_t*, const cuuint32_t*,
                             CUtensorMapInterleave, CUtensorMapSwizzle, CUtensorMapL2promotion, CUtensorMapFloatOOBfill);

}

extern "C" void kernel_launch(void* const* d_in, const int* in_sizes, int n_in, void* d_out, int out_size) {
    static EncodeFn enc = nullptr;
    if (!enc) {
        void* fn = nullptr;
        cudaDriverEntryPointQueryResult qr;
        cudaGetDriverEntryPoint("cuTensorMapEncodeTiled", &fn, cudaEnableDefault, &qr);
        enc = (EncodeFn)fn;
        cudaFuncSetAttribute(fused_kernel, cudaFuncAttributeMaxDynamicSharedMemorySize, SMEM_BYTES);
    }
    CUtensorMap mw1, mw2, mx;
    {
        cuuint32_t es[2] = {1, 1};
        cuuint64_t d1[2] = {FF_, D_}, s1[1] = {FF_ * 2};
        cuuint32_t b1[2] = {64, 64};
        enc(&mw1, CU_TENSOR_MAP_DATA_TYPE_BFLOAT16, 2, d_in[10], d1, s1, b1, es, CU_TENSOR_MAP_INTERLEAVE_NONE, CU_TENSOR_MAP_SWIZZLE_128B,
            CU_TENSOR_MAP_L2_PROMOTION_L2_128B, CU_TENSOR_MAP_FLOAT_OOB_FILL_NONE);
        cuuint64_t d2[2] = {D_, L_}, s2[1] = {D_ * 2};
        cuuint32_t b2[2] = {64, 128};
        enc(&mx, CU_TENSOR_MAP_DATA_TYPE_BFLOAT16, 2, d_in[0], d2, s2, b2, es, CU_TENSOR_MAP_INTERLEAVE_NONE, CU_TENSOR_MAP_SWIZZLE_128B,
            CU_TENSOR_MAP_L2_PROMOTION_L2_128B, CU_TENSOR_MAP_FLOAT_OOB_FILL_NONE);
        cuuint64_t d3[2] = {D_, FF_}, s3[1] = {D_ * 2};
        cuuint32_t b3[2] = {64, SL_};
        enc(&mw2, CU_TENSOR_MAP_DATA_TYPE_BFLOAT16, 2, d_in[11], d3, s3, b3, es, CU_TENSOR_MAP_INTERLEAVE_NONE, CU_TENSOR_MAP_SWIZZLE_128B,
            CU_TENSOR_MAP_L2_PROMOTION_L2_128B, CU_TENSOR_MAP_FLOAT_OOB_FILL_NONE);
    }
    Params p;
    p.x = (const __nv_bfloat16*)d_in[0];
    p.a_re = (const __nv_bfloat16*)d_in[1]; p.a_im = (const __nv_bfloat16*)d_in[2];
    p.b_re = (const __nv_bfloat16*)d_in[3]; p.b_im = (const __nv_bfloat16*)d_in[4];
    p.c_re = (const __nv_bfloat16*)d_in[5]; p.c_im = (const __nv_bfloat16*)d_in[6];
    p.log_dt = (const __nv_bfloat16*)d_in[7]; p.dskip = (const __nv_bfloat16*)d_in[8];
    p.out = (__nv_bfloat16*)d_out;
    fused_kernel<<<128, 512, SMEM_BYTES, cudaStreamPerThread>>>(mw1, mw2, mx, p);
}
```
